```python
import torch

def _softmax(x, axis=-1):
    return torch.softmax(x, dim=axis)

def _gelu(x):
    return torch.nn.functional.gelu(x, approximate='tanh')

def _silu(x):
    return torch.nn.functional.silu(x)

def _sigmoid(x):
    return torch.sigmoid(x)

def _layernorm(x, axis=-1, eps=1e-05):
    m = x.mean(dim=axis, keepdim=True)
    v = x.var(dim=axis, keepdim=True, unbiased=False)
    return (x - m) / torch.sqrt(v + eps)

def _scatter_add(tgt, idx, src, axis=0):
    return tgt.clone().index_add_(axis, idx, src)

def _segment_sum(src, seg, n):
    out = torch.zeros((n,) + src.shape[1:], dtype=src.dtype)
    return out.index_add_(0, seg, src)

def _pad(x, pw):
    flat = tuple((v for pair in reversed(pw) for v in pair))
    return torch.nn.functional.pad(x, flat)
kernel_name = 'standalone__kv_cache_quant_pre_rope_vs_post_rope__prompt'

def setup_inputs():

    _w = lambda a: (lambda t: t.to(torch.bfloat16) if t.is_floating_point() else t)(torch.as_tensor(a))
    B, Sq, Skv = (1, 2048, 2048)
    H, Dh0 = (8, 128)
    G = 64 if 64 > 0 else Dh0
    G = max(2, G // 2 * 2)
    Dh = max(G, Dh0 // G * G)
    Skv = max(Skv, Sq)
    ng = Dh // G
    bits = 3 if 3 > 1 else 4
    bits = max(2, min(8, bits))
    qmax = (1 << bits) - 1
    half = Dh // 2
    inv = 1.0 / 10000.0 ** (torch.arange(half) / max(1, half))
    ang_k = torch.arange(Skv)[:, None] * inv[None, :]
    ang_q = torch.arange(Skv - Sq, Skv)[:, None] * inv[None, :]
    kc = torch.cat([torch.cos(ang_k), torch.cos(ang_k)], dim=-1)
    ks = torch.cat([torch.sin(ang_k), torch.sin(ang_k)], dim=-1)
    qc = torch.cat([torch.cos(ang_q), torch.cos(ang_q)], dim=-1)
    qs = torch.cat([torch.sin(ang_q), torch.sin(ang_q)], dim=-1)
    qk_i = torch.randint(0, qmax + 1, (B, H, Skv, Dh)).to(torch.int32)
    qv_i = torch.randint(0, qmax + 1, (B, H, Skv, Dh)).to(torch.int32)
    ksc = torch.abs((lambda *s: torch.randn(*s, dtype=torch.bfloat16) * 0.4)(B, H, Skv, ng)) * 0.1 + 0.01
    kzp = torch.full((B, H, Skv, ng), qmax / 2.0)
    vsc = torch.abs((lambda *s: torch.randn(*s, dtype=torch.bfloat16) * 0.4)(B, H, Skv, ng)) * 0.1 + 0.01
    vzp = torch.full((B, H, Skv, ng), qmax / 2.0)
    return {'q': _w((lambda *s: torch.randn(*s, dtype=torch.bfloat16) * 6.4)(B, H, Sq, Dh) * 0.5), 'qk': _w(qk_i), 'k_scales': _w(ksc), 'k_zeros': _w(kzp), 'qv': _w(qv_i), 'v_scales': _w(vsc), 'v_zeros': _w(vzp), 'q_cos': _w(qc), 'q_sin': _w(qs), 'k_cos': _w(kc), 'k_sin': _w(ks)}

def reference(q, qk, k_scales, k_zeros, qv, v_scales, v_zeros, q_cos, q_sin, k_cos, k_sin):
    B, H, Sq, Dh = q.shape
    ng = k_scales.shape[-1]
    G = Dh // ng
    half = Dh // 2
    ks = (lambda x, n, axis: torch.repeat_interleave(x, n, dim=axis))(k_scales, G, axis=-1)
    kz = (lambda x, n, axis: torch.repeat_interleave(x, n, dim=axis))(k_zeros, G, axis=-1)
    k = ((lambda x, dt: x.to(dt))(qk, q.dtype) - kz) * ks
    vs = (lambda x, n, axis: torch.repeat_interleave(x, n, dim=axis))(v_scales, G, axis=-1)
    vz = (lambda x, n, axis: torch.repeat_interleave(x, n, dim=axis))(v_zeros, G, axis=-1)
    v = ((lambda x, dt: x.to(dt))(qv, q.dtype) - vz) * vs
    k1 = k[..., :half].clone()
    k2 = k[..., half:].clone()
    krh = torch.concatenate([-k2, k1], axis=-1)
    kr = k * k_cos[None, None, :, :] + krh * k_sin[None, None, :, :]
    q1 = q[..., :half].clone()
    q2 = q[..., half:].clone()
    qrh = torch.concatenate([-q2, q1], axis=-1)
    qr = q * q_cos[None, None, :, :] + qrh * q_sin[None, None, :, :]
    logits = torch.einsum('bhqd,bhkd->bhqk', qr, kr) * float(Dh) ** (-0.5)
    attn = _softmax(logits, axis=-1)
    out = torch.einsum('bhqk,bhkd->bhqd', attn, v)
    return out
```

```cpp
#include <cuda_runtime.h>
#include <cuda_bf16.h>
#include <stdint.h>
#include <type_traits>

#define SIGNAL_MODE 1
#define PREG 56
#define CREG 224
#define SUMTC 1
#define POLLGAP 0
#define POLL0 0
#define POLLW 8
#define IDLE_MODE 0
#define IDLE_NS 20000
#define MAXMODE 0
#define HACK1 0
#define TRACE_FULL 1
#define TRW 0
#define VEARLY 1
#define HACK2 0
#define PFENCE 0
#define AGG 1
#define PEEK 1
#define V0MODE 0
#define NSPLIT 0
#define ONESLATE 1
#define ESPLIT 9

namespace {

constexpr int kH = 8, kS = 2048, kD = 128;
constexpr int kItems = 33;
constexpr int kSlots = 4;
constexpr int kTileBytes = 32768;
constexpr int kDqWarps = 3;
constexpr int kRawBytes = 12288;
constexpr int kVSlotBytes = 49152;
constexpr int kSmemVOff = 2 * kTileBytes;
constexpr int kSmemRawOff = kSmemVOff + 2 * kVSlotBytes;
constexpr int kSmemOutOff = kSmemRawOff + kDqWarps * kRawBytes;
constexpr int kSmemBarOff = kSmemOutOff + kDqWarps * 2048;
constexpr int kON = SUMTC ? 68 : 64;
constexpr int kSmemBytes = kSmemBarOff + 256 + 1024;
constexpr float kScaleExact = 0.08838834764831845f * 1.4426950408889634f;
constexpr float kScale = MAXMODE ? 1.f : kScaleExact;
constexpr uint32_t kWaitLimit = 1u << 30;

__device__ __align__(1024) uint8_t g_scratch[(size_t)kH * kItems * kTileBytes];
#define FSTRIDE 64
constexpr int kFlagStride = FSTRIDE;
__device__ __align__(256) unsigned g_flags[kH * kItems * kFlagStride];
__device__ unsigned g_done;

#define TR(idx) do {} while (0)
#define TRG(idx) do {} while (0)

struct Params {
    const __nv_bfloat16* q;
    const int* qk;
    const __nv_bfloat16* k_scales;
    const __nv_bfloat16* k_zeros;
    const int* qv;
    const __nv_bfloat16* v_scales;
    const __nv_bfloat16* v_zeros;
    const __nv_bfloat16* q_cos;
    const __nv_bfloat16* q_sin;
    const __nv_bfloat16* k_cos;
    const __nv_bfloat16* k_sin;
    __nv_bfloat16* out;
    uint32_t zero, zero1, zero2, zero3;
    uint32_t t[8];
    uint32_t u[4];
};

__device__ __forceinline__ uint32_t smem_u32(const void* p) { return (uint32_t)__cvta_generic_to_shared(p); }

__device__ __forceinline__ uint32_t clock32() {
    uint32_t c;
    asm volatile("mov.u32 %0, %%clock;" : "=r"(c));
    return c;
}
__device__ __forceinline__ bool elect() {
    uint32_t r;
    asm volatile("{\n.reg .pred p;\nelect.sync _|p, 0xffffffff;\nselp.u32 %0, 1, 0, p;\n}\n" : "=r"(r));
    return r != 0;
}
__device__ __forceinline__ void mbar_init(uint32_t bar, uint32_t count) {
    asm volatile("mbarrier.init.shared::cta.b64 [%0], %1;" ::"r"(bar), "r"(count) : "memory");
}
__device__ __forceinline__ void mbar_expect_tx(uint32_t bar, uint32_t bytes) {
    asm volatile("mbarrier.arrive.expect_tx.shared::cta.b64 _, [%0], %1;" ::"r"(bar), "r"(bytes) : "memory");
}
__device__ __forceinline__ bool mbar_try(uint32_t bar, uint32_t parity) {
    uint32_t ok;
    asm volatile(
        "{\n.reg .pred p;\n"
        "mbarrier.try_wait.parity.shared::cta.b64 p, [%1], %2;\n"
        "selp.u32 %0, 1, 0, p;\n}\n"
        : "=r"(ok)
        : "r"(bar), "r"(parity)
        : "memory");
    return ok != 0;
}
__device__ __forceinline__ void mbar_wait(uint32_t bar, uint32_t parity) {
    if (mbar_try(bar, parity)) return;
    const uint32_t t0 = clock32();
    while (!mbar_try(bar, parity)) {
        if (clock32() - t0 > kWaitLimit) break;
    }
}
__device__ __forceinline__ void mbar_wait_idle(uint32_t bar, uint32_t parity) {
    if (mbar_try(bar, parity)) return;
    const uint32_t t0 = clock32();
    uint32_t ok;
    do {
        asm volatile(
            "{\n.reg .pred p;\n"
            "mbarrier.try_wait.parity.shared::cta.b64 p, [%1], %2, %3;\n"
            "selp.u32 %0, 1, 0, p;\n}\n"
            : "=r"(ok)
            : "r"(bar), "r"(parity), "r"(IDLE_NS)
            : "memory");
    } while (!ok && clock32() - t0 <= kWaitLimit);
}
__device__ __forceinline__ void mbar_arrive_cluster(uint32_t cluster_addr) {
    asm volatile("mbarrier.arrive.shared::cluster.b64 _, [%0];" ::"r"(cluster_addr) : "memory");
}
__device__ __forceinline__ uint32_t mapa(uint32_t addr, uint32_t rank) {
    uint32_t r;
    asm("mapa.shared::cluster.u32 %0, %1, %2;" : "=r"(r) : "r"(addr), "r"(rank));
    return r;
}
__device__ __forceinline__ void bulk_g2s(uint32_t dst, const void* src, uint32_t bytes, uint32_t bar) {
    asm volatile("cp.async.bulk.shared::cluster.global.mbarrier::complete_tx::bytes [%0], [%1], %2, [%3];" ::"r"(dst),
                 "l"(src), "r"(bytes), "r"(bar)
                 : "memory");
}
__device__ __forceinline__ void bulk_g2s_mc(uint32_t dst, const void* src, uint32_t bytes, uint32_t bar, uint16_t mask) {
    asm volatile(
        "cp.async.bulk.shared::cluster.global.mbarrier::complete_tx::bytes.multicast::cluster [%0], [%1], %2, [%3], %4;" ::"r"(dst),
        "l"(src), "r"(bytes), "r"(bar), "h"(mask)
        : "memory");
}
__device__ __forceinline__ void prefetch_l2(const void* src, uint32_t bytes) {
    asm volatile("cp.async.bulk.prefetch.L2.global [%0], %1;" ::"l"(src), "r"(bytes) : "memory");
}
__device__ __forceinline__ void bar_sync(int id, int n) { asm volatile("bar.sync %0, %1;" ::"r"(id), "r"(n) : "memory"); }
__device__ __forceinline__ void bar_arrive(int id, int n) { asm volatile("bar.arrive %0, %1;" ::"r"(id), "r"(n) : "memory"); }
__device__ __forceinline__ float ex2(float x) {
    float y;
    asm("ex2.approx.ftz.f32 %0, %1;" : "=f"(y) : "f"(x));
    return y;
}
__device__ __forceinline__ uint32_t pack_bf16(float lo, float hi) {
    uint32_t r;
    asm("cvt.rn.bf16x2.f32 %0, %1, %2;" : "=r"(r) : "f"(hi), "f"(lo));
    return r;
}
__device__ __forceinline__ uint32_t hmul2(uint32_t a, uint32_t b) {
    uint32_t r;
    asm("mul.rn.bf16x2 %0, %1, %2;" : "=r"(r) : "r"(a), "r"(b));
    return r;
}
__device__ __forceinline__ uint32_t hadd2(uint32_t a, uint32_t b) {
    uint32_t r;
    asm("add.rn.bf16x2 %0, %1, %2;" : "=r"(r) : "r"(a), "r"(b));
    return r;
}
__device__ __forceinline__ uint32_t hsub2(uint32_t a, uint32_t b) {
    uint32_t r;
    asm("sub.rn.bf16x2 %0, %1, %2;" : "=r"(r) : "r"(a), "r"(b));
    return r;
}
__device__ __forceinline__ uint32_t hfma2(uint32_t a, uint32_t b, uint32_t c) {
    uint32_t r;
    asm("fma.rn.bf16x2 %0, %1, %2, %3;" : "=r"(r) : "r"(a), "r"(b), "r"(c));
    return r;
}
__device__ __forceinline__ uint32_t prescale(uint32_t q) {
    if (!MAXMODE) return q;
    return hfma2(q, 0x3E033E03u, hmul2(q, 0xB9D8B9D8u));
}
__device__ __forceinline__ uint4 lds128(uint32_t a) {
    uint4 v;
    asm volatile("ld.shared.v4.u32 {%0,%1,%2,%3}, [%4];" : "=r"(v.x), "=r"(v.y), "=r"(v.z), "=r"(v.w) : "r"(a));
    return v;
}
__device__ __forceinline__ uint2 lds64(uint32_t a) {
    uint2 v;
    asm volatile("ld.shared.v2.u32 {%0,%1}, [%2];" : "=r"(v.x), "=r"(v.y) : "r"(a));
    return v;
}
__device__ __forceinline__ uint32_t lds32(uint32_t a) {
    uint32_t v;
    asm volatile("ld.shared.u32 %0, [%1];" : "=r"(v) : "r"(a));
    return v;
}
__device__ __forceinline__ void sts32(uint32_t a, uint32_t v) { asm volatile("st.shared.u32 [%0], %1;" ::"r"(a), "r"(v) : "memory"); }
__device__ __forceinline__ void mbar_arrive(uint32_t bar) {
    asm volatile("mbarrier.arrive.shared::cta.b64 _, [%0];" ::"r"(bar) : "memory");
}
__device__ __forceinline__ void bulk_s2g(void* dst, uint32_t src, uint32_t bytes) {
    asm volatile("cp.async.bulk.global.shared::cta.bulk_group [%0], [%1], %2;" ::"l"(dst), "r"(src), "r"(bytes) : "memory");
}
__device__ __forceinline__ bool bar_red_or(int id, int n, bool v) {
    uint32_t r;
    asm volatile(
        "{\n.reg .pred p, q;\nsetp.ne.u32 q, %3, 0;\n"
        "bar.red.or.pred p, %1, %2, q;\nselp.u32 %0, 1, 0, p;\n}\n"
        : "=r"(r)
        : "r"(id), "r"(n), "r"((uint32_t)v)
        : "memory");
    return r != 0;
}

#define WG_FENCE() asm volatile("wgmma.fence.sync.aligned;" ::: "memory")
#define WG_COMMIT() asm volatile("wgmma.commit_group.sync.aligned;" ::: "memory")
template <int N>
__device__ __forceinline__ void wg_wait() {
    asm volatile("wgmma.wait_group.sync.aligned %0;" ::"n"(N) : "memory");
}
#define ACC64(d)                                                                                                    \
    "+f"(d[0]), "+f"(d[1]), "+f"(d[2]), "+f"(d[3]), "+f"(d[4]), "+f"(d[5]), "+f"(d[6]), "+f"(d[7]), "+f"(d[8]),     \
        "+f"(d[9]), "+f"(d[10]), "+f"(d[11]), "+f"(d[12]), "+f"(d[13]), "+f"(d[14]), "+f"(d[15]), "+f"(d[16]),      \
        "+f"(d[17]), "+f"(d[18]), "+f"(d[19]), "+f"(d[20]), "+f"(d[21]), "+f"(d[22]), "+f"(d[23]), "+f"(d[24]),     \
        "+f"(d[25]), "+f"(d[26]), "+f"(d[27]), "+f"(d[28]), "+f"(d[29]), "+f"(d[30]), "+f"(d[31]), "+f"(d[32]),     \
        "+f"(d[33]), "+f"(d[34]), "+f"(d[35]), "+f"(d[36]), "+f"(d[37]), "+f"(d[38]), "+f"(d[39]), "+f"(d[40]),     \
        "+f"(d[41]), "+f"(d[42]), "+f"(d[43]), "+f"(d[44]), "+f"(d[45]), "+f"(d[46]), "+f"(d[47]), "+f"(d[48]),     \
        "+f"(d[49]), "+f"(d[50]), "+f"(d[51]), "+f"(d[52]), "+f"(d[53]), "+f"(d[54]), "+f"(d[55]), "+f"(d[56]),     \
        "+f"(d[57]), "+f"(d[58]), "+f"(d[59]), "+f"(d[60]), "+f"(d[61]), "+f"(d[62]), "+f"(d[63])
#define ACC64_STR                                                                                                   \
    "{%0,%1,%2,%3,%4,%5,%6,%7,%8,%9,%10,%11,%12,%13,%14,%15,%16,%17,%18,%19,%20,%21,%22,%23,%24,%25,%26,%27,%28,"   \
    "%29,%30,%31,%32,%33,%34,%35,%36,%37,%38,%39,%40,%41,%42,%43,%44,%45,%46,%47,%48,%49,%50,%51,%52,%53,%54,%55,"  \
    "%56,%57,%58,%59,%60,%61,%62,%63}"

template <int TB, int ACC>
__device__ __forceinline__ void wgmma_rs(float (&d)[64], uint32_t a0, uint32_t a1, uint32_t a2, uint32_t a3, uint64_t db) {
    asm volatile(
        "{\n.reg .pred p;\nsetp.ne.b32 p, %69, 0;\n"
        "wgmma.mma_async.sync.aligned.m64n128k16.f32.bf16.bf16 " ACC64_STR ", {%64,%65,%66,%67}, %68, p, 1, 1, %70;\n}\n"
        : ACC64(d)
        : "r"(a0), "r"(a1), "r"(a2), "r"(a3), "l"(db), "n"(ACC), "n"(TB));
}
__device__ __forceinline__ void wgmma_pv(float (&d)[68], uint32_t a0, uint32_t a1, uint32_t a2, uint32_t a3, uint64_t db) {
    asm volatile(
        "wgmma.mma_async.sync.aligned.m64n136k16.f32.bf16.bf16 {%0,%1,%2,%3,%4,%5,%6,%7,%8,%9,%10,%11,%12,%13,%14,%15,%16,%17,%18,%19,%20,%21,%22,%23,%24,%25,%26,%27,%28,%29,%30,%31,%32,%33,%34,%35,%36,%37,%38,%39,%40,%41,%42,%43,%44,%45,%46,%47,%48,%49,%50,%51,%52,%53,%54,%55,%56,%57,%58,%59,%60,%61,%62,%63,%64,%65,%66,%67}, {%68,%69,%70,%71}, %72, 1, 1, 1, 1;\n"
        : "+f"(d[0]), "+f"(d[1]), "+f"(d[2]), "+f"(d[3]), "+f"(d[4]), "+f"(d[5]), "+f"(d[6]), "+f"(d[7]), "+f"(d[8]), "+f"(d[9]), "+f"(d[10]), "+f"(d[11]), "+f"(d[12]), "+f"(d[13]), "+f"(d[14]), "+f"(d[15]), "+f"(d[16]), "+f"(d[17]), "+f"(d[18]), "+f"(d[19]), "+f"(d[20]), "+f"(d[21]), "+f"(d[22]), "+f"(d[23]), "+f"(d[24]), "+f"(d[25]), "+f"(d[26]), "+f"(d[27]), "+f"(d[28]), "+f"(d[29]), "+f"(d[30]), "+f"(d[31]), "+f"(d[32]), "+f"(d[33]), "+f"(d[34]), "+f"(d[35]), "+f"(d[36]), "+f"(d[37]), "+f"(d[38]), "+f"(d[39]), "+f"(d[40]), "+f"(d[41]), "+f"(d[42]), "+f"(d[43]), "+f"(d[44]), "+f"(d[45]), "+f"(d[46]), "+f"(d[47]), "+f"(d[48]), "+f"(d[49]), "+f"(d[50]), "+f"(d[51]), "+f"(d[52]), "+f"(d[53]), "+f"(d[54]), "+f"(d[55]), "+f"(d[56]), "+f"(d[57]), "+f"(d[58]), "+f"(d[59]), "+f"(d[60]), "+f"(d[61]), "+f"(d[62]), "+f"(d[63]), "+f"(d[64]), "+f"(d[65]), "+f"(d[66]), "+f"(d[67])
        : "r"(a0), "r"(a1), "r"(a2), "r"(a3), "l"(db));
}
__device__ __forceinline__ void wgmma_pv(float (&d)[64], uint32_t a0, uint32_t a1, uint32_t a2, uint32_t a3, uint64_t db) {
    wgmma_rs<1, 1>(d, a0, a1, a2, a3, db);
}
__device__ __forceinline__ void wgmma_pv_hi(float (&d)[68], uint32_t a0, uint32_t a1, uint32_t a2, uint32_t a3, uint64_t db) {
    asm volatile(
        "wgmma.mma_async.sync.aligned.m64n72k16.f32.bf16.bf16 {%0,%1,%2,%3,%4,%5,%6,%7,%8,%9,%10,%11,%12,%13,%14,%15,%16,%17,%18,%19,%20,%21,%22,%23,%24,%25,%26,%27,%28,%29,%30,%31,%32,%33,%34,%35}, {%36,%37,%38,%39}, %40, 1, 1, 1, 1;\n"
        : "+f"(d[32]), "+f"(d[33]), "+f"(d[34]), "+f"(d[35]), "+f"(d[36]), "+f"(d[37]), "+f"(d[38]), "+f"(d[39]), "+f"(d[40]), "+f"(d[41]), "+f"(d[42]), "+f"(d[43]), "+f"(d[44]), "+f"(d[45]), "+f"(d[46]), "+f"(d[47]), "+f"(d[48]), "+f"(d[49]), "+f"(d[50]), "+f"(d[51]), "+f"(d[52]), "+f"(d[53]), "+f"(d[54]), "+f"(d[55]), "+f"(d[56]), "+f"(d[57]), "+f"(d[58]), "+f"(d[59]), "+f"(d[60]), "+f"(d[61]), "+f"(d[62]), "+f"(d[63]), "+f"(d[64]), "+f"(d[65]), "+f"(d[66]), "+f"(d[67])
        : "r"(a0), "r"(a1), "r"(a2), "r"(a3), "l"(db));
}
__device__ __forceinline__ void wgmma_pv_lo(float (&d)[68], uint32_t a0, uint32_t a1, uint32_t a2, uint32_t a3, uint64_t db) {
    asm volatile(
        "wgmma.mma_async.sync.aligned.m64n64k16.f32.bf16.bf16 {%0,%1,%2,%3,%4,%5,%6,%7,%8,%9,%10,%11,%12,%13,%14,%15,%16,%17,%18,%19,%20,%21,%22,%23,%24,%25,%26,%27,%28,%29,%30,%31}, {%32,%33,%34,%35}, %36, 1, 1, 1, 1;\n"
        : "+f"(d[0]), "+f"(d[1]), "+f"(d[2]), "+f"(d[3]), "+f"(d[4]), "+f"(d[5]), "+f"(d[6]), "+f"(d[7]), "+f"(d[8]), "+f"(d[9]), "+f"(d[10]), "+f"(d[11]), "+f"(d[12]), "+f"(d[13]), "+f"(d[14]), "+f"(d[15]), "+f"(d[16]), "+f"(d[17]), "+f"(d[18]), "+f"(d[19]), "+f"(d[20]), "+f"(d[21]), "+f"(d[22]), "+f"(d[23]), "+f"(d[24]), "+f"(d[25]), "+f"(d[26]), "+f"(d[27]), "+f"(d[28]), "+f"(d[29]), "+f"(d[30]), "+f"(d[31])
        : "r"(a0), "r"(a1), "r"(a2), "r"(a3), "l"(db));
}
template <int N>
__device__ __forceinline__ void fence_regs(float (&d)[N]) {
#pragma unroll
    for (int i = 0; i < N; i++) asm volatile("" : "+f"(d[i])::"memory");
}
__device__ __forceinline__ void fence_regs(uint32_t (&d)[32]) {
#pragma unroll
    for (int i = 0; i < 32; i++) asm volatile("" : "+r"(d[i])::"memory");
}
constexpr int kVGroup = SUMTC ? 3072 : 2048;
constexpr uint64_t kDescK = (uint64_t(1) << 62) | (uint64_t(2048 >> 4) << 32) | (uint64_t(1) << 16);
constexpr uint64_t kDescV = (uint64_t(1) << 62) | (uint64_t(kVGroup >> 4) << 32) | (uint64_t(1024 >> 4) << 16);

template <int ACC = 0>
__device__ __forceinline__ void gemm_qk(float (&s)[64], const uint32_t (&q)[32], uint64_t d) {
    wgmma_rs<0, ACC>(s, q[0], q[1], q[2], q[3], d);
#pragma unroll
    for (int kk = 1; kk < 8; kk++)
        wgmma_rs<0, 1>(s, q[4 * kk], q[4 * kk + 1], q[4 * kk + 2], q[4 * kk + 3], d + (((kk >> 2) * 1024 + (kk & 3) * 32) >> 4));
}
__device__ __forceinline__ void gemm_pv(float (&o)[kON], const uint32_t (&p)[32], uint64_t d) {
#pragma unroll
    for (int kk = 0; kk < 8; kk++) wgmma_pv(o, p[4 * kk], p[4 * kk + 1], p[4 * kk + 2], p[4 * kk + 3], d + ((kk * 2 * kVGroup) >> 4));
}
__device__ __forceinline__ uint32_t opaque(uint32_t v) {
    asm volatile("mov.b32 %0, %0;" : "+r"(v));
    return v;
}

struct DqIn { uint4 lo, hi; uint2 cl, ch, sl, sh; };
template <bool IS_V>
__device__ __forceinline__ void dq_load(DqIn& x, uint32_t ia, uint32_t ca) {
    x.lo = lds128(ia); x.hi = lds128(ia + 256);
    if (!IS_V) { x.cl = lds64(ca); x.ch = lds64(ca + 128); x.sl = lds64(ca + 2048); x.sh = lds64(ca + 2048 + 128); }
}
template <bool IS_V>
__device__ __forceinline__ void dequant_slice(uint32_t ia, uint32_t ca, uint32_t oa, uint32_t sc, uint32_t zp) {
    const uint32_t s0 = __byte_perm(sc, 0, 0x1010), s1 = __byte_perm(sc, 0, 0x3232);
    const uint32_t z0 = __byte_perm(zp, 0, 0x1010), z1 = __byte_perm(zp, 0, 0x3232);
    DqIn x[2];
    dq_load<IS_V>(x[0], ia, ca);
#pragma unroll
    for (int it = 0; it < 4; it++) {
        const DqIn& a = x[it & 1];
        uint32_t v0 = hmul2(hsub2(pack_bf16((float)(int)a.lo.x, (float)(int)a.lo.y), z0), s0);
        uint32_t v1 = hmul2(hsub2(pack_bf16((float)(int)a.lo.z, (float)(int)a.lo.w), z0), s0);
        uint32_t v2 = hmul2(hsub2(pack_bf16((float)(int)a.hi.x, (float)(int)a.hi.y), z1), s1);
        uint32_t v3 = hmul2(hsub2(pack_bf16((float)(int)a.hi.z, (float)(int)a.hi.w), z1), s1);
        if (it < 3) dq_load<IS_V>(x[(it + 1) & 1], ia ^ (((it + 1) >> 1) * 128 + ((it + 1) & 1) * 16), ca ^ (((it + 1) >> 1) * 64 + ((it + 1) & 1) * 8));
        if (!IS_V) {
            const uint32_t r0 = hsub2(hmul2(v0, a.cl.x), hmul2(v2, a.sl.x));
            const uint32_t r1 = hsub2(hmul2(v1, a.cl.y), hmul2(v3, a.sl.y));
            const uint32_t r2 = hadd2(hmul2(v2, a.ch.x), hmul2(v0, a.sh.x));
            const uint32_t r3 = hadd2(hmul2(v3, a.ch.y), hmul2(v1, a.sh.y));
            v0 = r0; v1 = r1; v2 = r2; v3 = r3;
        }
        const uint32_t o0 = oa ^ (it << 5), o1 = oa ^ ((it << 5) | 16);
        sts32(o0, v0); sts32(o1, v1); sts32(o0 + 1024, v2); sts32(o1 + 1024, v3);
    }
}

__device__ __forceinline__ void publish(unsigned* flag, uint32_t seen, uint32_t zero, int lane) {
    const uint32_t one = 1u + (__reduce_or_sync(0xffffffffu, seen) & zero);
    if (elect()) asm volatile("red.relaxed.gpu.global.add.u32 [%0], %1;" ::"l"(flag), "r"(one) : "memory");
}
__device__ __forceinline__ uint32_t ld_back(const void* p) {
    uint32_t v = 0;
    asm volatile("ld.relaxed.gpu.global.u32 %0, [%1];" : "=r"(v) : "l"(p) : "memory");
    return v;
}

__device__ __forceinline__ uint4 ldg128(const void* p) {
    uint4 v;
    asm volatile("ld.global.nc.L1::no_allocate.v4.u32 {%0,%1,%2,%3}, [%4];" : "=r"(v.x), "=r"(v.y), "=r"(v.z), "=r"(v.w) : "l"(p) : "memory");
    return v;
}
__device__ __forceinline__ uint2 ldg64(const void* p) {
    uint2 v;
    asm volatile("ld.global.nc.L1::no_allocate.v2.u32 {%0,%1}, [%2];" : "=r"(v.x), "=r"(v.y) : "l"(p) : "memory");
    return v;
}
__device__ __forceinline__ uint32_t ldg32(const void* p) {
    uint32_t v;
    asm volatile("ld.global.nc.L1::no_allocate.u32 %0, [%1];" : "=r"(v) : "l"(p) : "memory");
    return v;
}
struct FirstIn { uint4 lo, hi; uint2 cl, ch, sl, sh; uint32_t sc, zp; };
template <bool IS_V>
__device__ __forceinline__ void first_load(FirstIn& x, const Params& p, int h, int row, int mp) {
    const int hr = h * kS + row;
    const int* ints = (IS_V ? p.qv : p.qk) + hr * kD + 4 * mp;
    x.lo = ldg128(ints); x.hi = ldg128(ints + 64);
    if (!IS_V) {
        x.cl = ldg64(p.k_cos + row * kD + 4 * mp); x.ch = ldg64(p.k_cos + row * kD + 64 + 4 * mp);
        x.sl = ldg64(p.k_sin + row * kD + 4 * mp); x.sh = ldg64(p.k_sin + row * kD + 64 + 4 * mp);
    }
    x.sc = ldg32((IS_V ? p.v_scales : p.k_scales) + hr * 2); x.zp = ldg32((IS_V ? p.v_zeros : p.k_zeros) + hr * 2);
}
template <bool IS_V>
__device__ __forceinline__ uint32_t first_store(const FirstIn& a, uint8_t* slice, int r, int mp) {
    const int j = mp >> 3, c = (mp >> 1) & 3, b = mp & 1;
    const uint32_t s0 = __byte_perm(a.sc, 0, 0x1010), s1 = __byte_perm(a.sc, 0, 0x3232);
    const uint32_t z0 = __byte_perm(a.zp, 0, 0x1010), z1 = __byte_perm(a.zp, 0, 0x3232);
    uint32_t v0 = hmul2(hsub2(pack_bf16((float)(int)a.lo.x, (float)(int)a.lo.y), z0), s0);
    uint32_t v1 = hmul2(hsub2(pack_bf16((float)(int)a.lo.z, (float)(int)a.lo.w), z0), s0);
    uint32_t v2 = hmul2(hsub2(pack_bf16((float)(int)a.hi.x, (float)(int)a.hi.y), z1), s1);
    uint32_t v3 = hmul2(hsub2(pack_bf16((float)(int)a.hi.z, (float)(int)a.hi.w), z1), s1);
    if (!IS_V) {
        const uint32_t r0 = hsub2(hmul2(v0, a.cl.x), hmul2(v2, a.sl.x)), r1 = hsub2(hmul2(v1, a.cl.y), hmul2(v3, a.sl.y));
        const uint32_t r2 = hadd2(hmul2(v2, a.ch.x), hmul2(v0, a.sh.x)), r3 = hadd2(hmul2(v3, a.ch.y), hmul2(v1, a.sh.y));
        v0 = r0; v1 = r1; v2 = r2; v3 = r3;
    }
    const bool c0 = c & 1, c1 = c & 2;
    uint32_t x = __shfl_xor_sync(0xffffffffu, c0 ? v0 : v1, 2), y = __shfl_xor_sync(0xffffffffu, c0 ? v2 : v3, 2);
    const uint32_t a0 = c0 ? x : v0, a1 = c0 ? v1 : x, a2 = c0 ? y : v2, a3 = c0 ? v3 : y;
    x = __shfl_xor_sync(0xffffffffu, c1 ? a0 : a2, 4); y = __shfl_xor_sync(0xffffffffu, c1 ? a1 : a3, 4);
    uint8_t* dst = slice + (c >> 1) * 1024 + r * 128 + (((4 * j + 2 * b + (c & 1)) ^ r) << 4);
    *reinterpret_cast<uint4*>(dst) = make_uint4(c1 ? x : a0, c1 ? y : a1, c1 ? a2 : x, c1 ? a3 : y);
    return ld_back(dst);
}

template <bool SUM, int N0, int N1, bool SHIFT = true>
__device__ __forceinline__ void exp_tile(float (&s)[64], float ms0, float ms1, float& l0, float& l1) {
    if (N0 == 0 && SHIFT) {
#pragma unroll
        for (int i = 0; i < 64; i++) s[i] = fmaf(s[i], kScale, (i & 2) ? -ms1 : -ms0);
    }
    float u0 = 0.f, u1 = 0.f;
#pragma unroll
    for (int n = N0; n < N1; n++) {
        s[4 * n] = ex2(s[4 * n]); s[4 * n + 1] = ex2(s[4 * n + 1]);
        s[4 * n + 2] = ex2(s[4 * n + 2]); s[4 * n + 3] = ex2(s[4 * n + 3]);
        if (SUM) {
            l0 += s[4 * n]; l1 += s[4 * n + 2];
            if (n == N0) { u0 = s[4 * n + 1]; u1 = s[4 * n + 3]; } else { u0 += s[4 * n + 1]; u1 += s[4 * n + 3]; }
        }
    }
    if (SUM) { l0 += u0; l1 += u1; }
}
__device__ __forceinline__ void row_max(const float (&s)[64], float& m0, float& m1) {
    float a0 = fmaxf(s[0], s[1]), a1 = fmaxf(s[2], s[3]), b0 = fmaxf(s[4], s[5]), b1 = fmaxf(s[6], s[7]);
#pragma unroll
    for (int n = 2; n < 16; n += 2) {
        a0 = fmaxf(a0, fmaxf(s[4 * n], s[4 * n + 1])); a1 = fmaxf(a1, fmaxf(s[4 * n + 2], s[4 * n + 3]));
        b0 = fmaxf(b0, fmaxf(s[4 * n + 4], s[4 * n + 5])); b1 = fmaxf(b1, fmaxf(s[4 * n + 6], s[4 * n + 7]));
    }
    m0 = fmaxf(a0, b0); m1 = fmaxf(a1, b1);
    m0 = fmaxf(m0, __shfl_xor_sync(0xffffffffu, m0, 1)); m1 = fmaxf(m1, __shfl_xor_sync(0xffffffffu, m1, 1));
    m0 = fmaxf(m0, __shfl_xor_sync(0xffffffffu, m0, 2)); m1 = fmaxf(m1, __shfl_xor_sync(0xffffffffu, m1, 2));
}
__device__ __forceinline__ void pack_tile(uint32_t (&pr)[32], const float (&s)[64]) {
#pragma unroll
    for (int i = 0; i < 32; i++) pr[i] = pack_bf16(s[2 * i], s[2 * i + 1]);
}
template <int J0, int J1>
__device__ __forceinline__ void store_cols(__nv_bfloat16* op, uint4 (&v)[8], const float (&o)[kON], float i0, float i1) {
#pragma unroll
    for (int j = J0; j < J1; j++) {
        uint4 &v0 = v[2 * j], &v1 = v[2 * j + 1];
        v0.x = pack_bf16(o[16 * j] * i0, o[16 * j + 1] * i0);       v0.y = pack_bf16(o[16 * j + 4] * i0, o[16 * j + 5] * i0);
        v0.z = pack_bf16(o[16 * j + 8] * i0, o[16 * j + 9] * i0);   v0.w = pack_bf16(o[16 * j + 12] * i0, o[16 * j + 13] * i0);
        *reinterpret_cast<uint4*>(op + 32 * j) = v0;
        v1.x = pack_bf16(o[16 * j + 2] * i1, o[16 * j + 3] * i1);   v1.y = pack_bf16(o[16 * j + 6] * i1, o[16 * j + 7] * i1);
        v1.z = pack_bf16(o[16 * j + 10] * i1, o[16 * j + 11] * i1); v1.w = pack_bf16(o[16 * j + 14] * i1, o[16 * j + 15] * i1);
        *reinterpret_cast<uint4*>(op + 8 * kD + 32 * j) = v1;
    }
}
__device__ __forceinline__ bool all_finite(const uint4 (&v)[8], uint32_t zero) {
    uint32_t a[4] = {0, 0, 0, 0};
#pragma unroll
    for (int j = 0; j < 8; j++) {
        a[0] = hfma2(v[j].x, zero, a[0]); a[1] = hfma2(v[j].y, zero, a[1]);
        a[2] = hfma2(v[j].z, zero, a[2]); a[3] = hfma2(v[j].w, zero, a[3]);
    }
    return ((a[0] | a[1] | a[2] | a[3]) & 0x7fff7fffu) == 0;
}
__device__ __forceinline__ void sched_boundary(uint32_t zero) {
    asm volatile("{\n.reg .pred p;\nsetp.ne.u32 p, %0, 0;\n@p exit;\n}\n" ::"r"(zero) : "memory");
}
__device__ __forceinline__ float rcp(float x) {
    float y;
    asm("rcp.approx.ftz.f32 %0, %1;" : "=f"(y) : "f"(x));
    return y;
}

__global__ void __cluster_dims__(2, 1, 1) __launch_bounds__(384, 1) attn_kernel(const __grid_constant__ Params p) {
    extern __shared__ uint8_t smem_raw[];
    const uint32_t sbase = (smem_u32(smem_raw) + 1023) & ~1023u;
    const uint32_t bar_full = sbase + kSmemBarOff;
    const uint32_t bar_empty = bar_full + 8 * kSlots;
    const uint32_t bar_raw = bar_empty + 8 * kSlots;
    const uint32_t bar_qfull = bar_raw + 16 * kDqWarps;
    const uint32_t bar_fb = bar_qfull + 64;

    const int warp = __shfl_sync(0xffffffffu, threadIdx.x >> 5, 0), lane = threadIdx.x & 31;
    const int h = blockIdx.x >> 4, qt = blockIdx.x & 15;

    if (warp >= 8) {
        asm volatile("setmaxnreg.dec.sync.aligned.u32 %0;" ::"n"(PREG));
        if (warp == 8) {
            TR(0); TRG(1);
            if (lane == 0) {
                for (int i = 0; i < kSlots; i++) {
                    mbar_init(bar_full + 8 * i, 1);
                    mbar_init(bar_empty + 8 * i, 16);
                }
                mbar_init(bar_fb, 1);
                asm volatile("fence.mbarrier_init.release.cluster;" ::: "memory");
            }
            __syncwarp();
            asm volatile("barrier.cluster.arrive.relaxed.aligned;" ::: "memory");
            asm volatile("barrier.cluster.wait.acquire.aligned;" ::: "memory");
            const uint32_t rank = blockIdx.x & 1;
            const uint8_t* src = g_scratch + (size_t)h * kItems * kTileBytes + rank * (kTileBytes / 2);
            uint32_t ready = 0, parity = 3;
#pragma unroll 1
            for (int n = 0; n < kItems; n++, ready >>= 1, src += kTileBytes) {
                if (n == kItems - 2) continue;
                if (!(ready & 1)) {
                    const uint32_t t0 = clock32();
                    const unsigned* fp = g_flags + (h * kItems + n + lane) * kFlagStride;
                    const uint32_t need = n + lane < 2 ? 64 : V0MODE && n + lane == 2 ? 32 : 16;
                    const bool mine = lane < (n < 3 ? 3 - n : POLLW) && n + lane < kItems;
                    if (n == 0) { while (clock32() - t0 < p.u[0]) {} }
                    while (true) {
                        const uint32_t t1 = clock32();
                        uint32_t v = 0;
                        if (mine) asm volatile("ld.relaxed.gpu.global.u32 %0, [%1];" : "=r"(v) : "l"(fp) : "memory");
                        ready = __ballot_sync(0xffffffffu, v >= need);
                        if ((ready & 1) || __any_sync(0xffffffffu, t1 - t0 > kWaitLimit)) break;
                        while (clock32() - t1 < p.u[1]) __nanosleep(32);
                    }
                    asm volatile("fence.acquire.gpu;" ::: "memory");
                    if (PFENCE) asm volatile("fence.proxy.async.global;" ::: "memory");
                }
                if (TRACE_FULL) TR(128 + (n & 31));
                const bool is_v = n != 0 && !(n & 1);
                const int odd = ((n + 1) >> 1) & 1 ^ (is_v ? 1 : 0);
                const int slot = (is_v ? 2 : 0) + odd;
                uint32_t ahead = 0;
                const bool peek = PEEK && !(ready & 2);
                if (peek && lane >= 1 && lane < POLLW && n + lane < kItems)
                    asm volatile("ld.relaxed.gpu.global.u32 %0, [%1];" : "=r"(ahead) : "l"(g_flags + (h * kItems + n + lane) * kFlagStride) : "memory");
                mbar_wait_idle(bar_empty + 8 * slot, (parity >> slot) & 1);
                if (TRACE_FULL) TR(160 + (n & 31));
                if (elect()) {
                    mbar_expect_tx(bar_full + 8 * slot, kTileBytes);
                    if (SUMTC && is_v && !HACK1) {
                        const uint32_t dst = sbase + kSmemVOff + odd * kVSlotBytes + rank * 8 * kVGroup;
#pragma unroll
                        for (int gi = 0; gi < 8; gi++) bulk_g2s_mc(dst + gi * kVGroup, src + gi * 2048, 2048, bar_full + 8 * slot, (uint16_t)3);
                    } else {
                        const uint32_t dst = sbase + (is_v ? kSmemVOff + odd * kVSlotBytes : odd * kTileBytes);
                        bulk_g2s_mc(dst + rank * (kTileBytes / 2), src, kTileBytes / 2, bar_full + 8 * slot, (uint16_t)3);
                    }
                }
                parity ^= 1u << slot;
                if (peek) {
                    ready |= __ballot_sync(0xffffffffu, ahead >= (n + lane < 2 ? 64u : V0MODE && n + lane == 2 ? 32u : 16u));
                    asm volatile("fence.acquire.gpu;" ::: "memory");
                    if (PFENCE) asm volatile("fence.proxy.async.global;" ::: "memory");
                }
            }
            uint32_t ticket = 0;
            if (lane == 0) ticket = atomicAdd(&g_done, 1u);
            ticket = __shfl_sync(0xffffffffu, ticket, 0);
            if (ticket == gridDim.x - 1) {
                for (int i = lane; i < kH * kItems; i += 32) g_flags[i * kFlagStride] = 0;
                if (lane == 0) g_done = 0;
            }
        } else {
            const int w = warp - 9;
            const uint32_t t_start = clock32();
            const int first = (w == 0 ? 2 : 5 - w) + V0MODE;
            const uint32_t my_bar = bar_raw + 16 * w;
            const uint32_t my_raw = sbase + kSmemRawOff + w * kRawBytes;
            const uint32_t my_out = sbase + kSmemOutOff + w * 2048;
            const int r = lane >> 2, c = lane & 3;
            uint32_t sc_next, zp_next;
            auto issue = [&](int n, auto tag) {
                constexpr bool is_v = decltype(tag)::value;
                const int row0 = (is_v ? (n >> 1) - 1 : (n + 1) >> 1) * 128 + qt * 8;
                const int hr = h * kS + row0;
                if (elect()) {
                    if (is_v) {
                        mbar_expect_tx(my_bar + 8, 4096);
                        bulk_g2s(my_raw + 8192, p.qv + hr * kD, 4096, my_bar + 8);
                    } else {
                        mbar_expect_tx(my_bar, 8192);
                        bulk_g2s(my_raw, p.qk + hr * kD, 4096, my_bar);
                        bulk_g2s(my_raw + 4096, p.k_cos + row0 * kD, 2048, my_bar);
                        bulk_g2s(my_raw + 6144, p.k_sin + row0 * kD, 2048, my_bar);
                    }
                }
                sc_next = ldg32(reinterpret_cast<const uint32_t*>(is_v ? p.v_scales : p.k_scales) + hr + r);
                zp_next = ldg32(reinterpret_cast<const uint32_t*>(is_v ? p.v_zeros : p.k_zeros) + hr + r);
            };
            if (elect()) {
                mbar_init(my_bar, 1); mbar_init(my_bar + 8, 1);
                if (w == 1) for (int i = 0; i < 8; i++) mbar_init(bar_qfull + 8 * i, 1);
                asm volatile("fence.mbarrier_init.release.cluster;" ::: "memory");
            }
            __syncwarp();
            asm volatile("barrier.cluster.arrive.relaxed.aligned;" ::: "memory");
            if (V0MODE && w != 1) {
                const int r = 2 * w + (lane >> 4), mp = lane & 15;
                uint8_t* slice = g_scratch + (size_t)(h * kItems + 2) * kTileBytes + qt * 2048;
                FirstIn a, b;
                first_load<true>(a, p, h, qt * 8 + r, mp);
                first_load<true>(b, p, h, qt * 8 + r + 2, mp);
                const uint32_t seen = first_store<true>(a, slice, r, mp);
                publish(g_flags + (h * kItems + 2) * kFlagStride, seen | first_store<true>(b, slice, r + 2, mp), p.zero, lane);
                TR(226);
            }
            if (w == 1) {
#pragma unroll 1
                for (int k = 0; k < 8; k++) {
                    const int row = qt * 128 + k * 16;
                    const uint32_t bar = bar_qfull + 8 * k, dst = sbase + kSmemVOff + (k >> 2) * kVSlotBytes + (k & 3) * 4096;
                    while (clock32() - t_start < p.t[1] + k * p.t[2] + (k >> 2) * p.t[6]) {}
                    if (elect()) {
                        mbar_expect_tx(bar, 3 * 4096);
                        bulk_g2s(dst, p.q + (h * kS + row) * kD, 4096, bar);
                        bulk_g2s(dst + 16384, p.q_cos + row * kD, 4096, bar);
                        bulk_g2s(dst + 32768, p.q_sin + row * kD, 4096, bar);
                    }
                }
                TR(10);
            }
            while (clock32() - t_start < (w == 0 ? p.t[0] : w == 1 ? p.t[7] : p.t[5])) {}
            if (first & 1) issue(first, std::false_type{}); else issue(first, std::true_type{});
            const uint32_t x = r & 3;
            const uint32_t ia = my_raw + r * 512 + c * 32 + (x >> 1) * 128 + (x & 1) * 16;
            const uint32_t ca = my_raw + 4096 + r * 256 + c * 16 + (x >> 1) * 64 + (x & 1) * 8;
            const uint32_t oa = my_out + r * 128 + c * 4 + (((2 * x) ^ r) << 4);
            uint8_t* dst = g_scratch + (size_t)(h * kItems + first) * kTileBytes + qt * 2048;
            unsigned* flag = g_flags + (h * kItems + first) * kFlagStride;
            const int last = first == 4 ? 28 : kItems - 1;
            uint32_t round = 0;
            auto item = [&](int n, auto is_v) {
                constexpr bool V = decltype(is_v)::value;
                const uint32_t sc = sc_next, zp = zp_next;
                mbar_wait_idle(my_bar + (V ? 8 : 0), round >> 1);
                if (TRACE_FULL) TR(192 + (n & 31));
                if (round != 0 && n + kDqWarps <= last) issue(n + kDqWarps, std::integral_constant<bool, !V>{});
                dequant_slice<V>(ia + (V ? 8192 : 0), ca, oa, sc, zp);
                __syncwarp();
                {
                    const uint4 v0 = lds128(my_out + lane * 16), v1 = lds128(my_out + 512 + lane * 16);
                    const uint4 v2 = lds128(my_out + 1024 + lane * 16), v3 = lds128(my_out + 1536 + lane * 16);
                    uint4* d = reinterpret_cast<uint4*>(dst) + lane;
                    d[0] = v0; d[32] = v1; d[64] = v2; d[96] = v3;
                }
                if (TRACE_FULL) TR(256 + (n & 31));
                publish(flag, ld_back(dst + lane * 64), p.zero, lane);
                if (TRACE_FULL || n >= 28) TR(224 + (n & 31));
                if (round == 0) {
                    while (clock32() - t_start < p.t[3] + (first - 2 - V0MODE) * p.t[4]) __nanosleep(64);
                    issue(n + kDqWarps, std::integral_constant<bool, !V>{});
                }
            };
#pragma unroll 1
            for (int n = first; n <= last; n += kDqWarps, round++, dst += (size_t)kDqWarps * kTileBytes, flag += kDqWarps * kFlagStride) {
                if (n & 1) item(n, std::false_type{}); else item(n, std::true_type{});
            }
            asm volatile("barrier.cluster.wait.aligned;" ::: "memory");
        }
    } else {
        const uint32_t t_start = clock32();
        asm volatile("barrier.cluster.arrive.relaxed.aligned;" ::: "memory");
        asm volatile("setmaxnreg.inc.sync.aligned.u32 %0;" ::"n"(CREG));
        const int wg = warp >> 2;
        const int g = lane >> 2, c = lane & 3;
        const uint32_t rel_addr = mapa(bar_empty, lane & 1);
        const uint32_t q_stage = sbase + kSmemVOff + wg * kVSlotBytes + (warp & 3) * 4096;
        {
            const int r = 2 * (warp & 3) + (lane >> 4), mp = lane & 15;
            FirstIn k;
            first_load<false>(k, p, h, wg * 128 + qt * 8 + r, mp);
            TR(320 + warp);
            const uint32_t seen = first_store<false>(k, g_scratch + (size_t)(h * kItems + wg) * kTileBytes + qt * 2048, r, mp);
            TR(328 + warp);
            const bool never = bar_red_or(4 + wg, 128, (seen & p.zero) != 0);
            if ((threadIdx.x & 127) == 0)
                asm volatile("red.relaxed.gpu.global.add.u32 [%0], %1;" ::"l"(g_flags + (h * kItems + wg) * kFlagStride), "r"(never ? 0u : 4u) : "memory");
            TR(336 + warp);
        }
        if ((warp & 3) == 1) TR(224 + wg);
        asm volatile("barrier.cluster.wait.acquire.aligned;" ::: "memory");

        auto write_ones = [&](int vslot) {
            const int t = threadIdx.x & 127;
            asm volatile("st.shared.v4.u32 [%0], {%1,%1,%1,%1};" ::"r"(sbase + kSmemVOff + vslot * kVSlotBytes + (t >> 3) * kVGroup + 2048 + (t & 7) * 144),
                         "r"(0x3F803F80u) : "memory");
            asm volatile("fence.proxy.async.shared::cta;" ::: "memory");
        };
        if (lane < 2) mbar_arrive_cluster(rel_addr + 8 * (3 - wg));

        uint32_t q[32];
        {
            mbar_wait(bar_qfull + 8 * warp, 0);
            if ((warp & 3) == 3) TR(12 + wg);
            TR(344 + warp);
            const bool odd = g & 1;
            const uint32_t a = q_stage + g * 256 + c * 16;
            uint32_t t[2][4][4];
#pragma unroll
            for (int r = 0; r < 2; r++) {
#pragma unroll
                for (int j = 0; j < 2; j++) {
                    const uint32_t b = a + r * 2048 + ((j * 64) ^ (odd ? 64 : 0));
                    const uint4 lo = lds128(b), hi = lds128(b + 128);
                    const uint4 cl = lds128(b + 16384), ch = lds128(b + 16384 + 128);
                    const uint4 sl = lds128(b + 32768), sh = lds128(b + 32768 + 128);
                    t[r][j][0] = hsub2(hmul2(lo.x, cl.x), hmul2(hi.x, sl.x)); t[r][j + 2][0] = hadd2(hmul2(hi.x, ch.x), hmul2(lo.x, sh.x));
                    t[r][j][1] = hsub2(hmul2(lo.y, cl.y), hmul2(hi.y, sl.y)); t[r][j + 2][1] = hadd2(hmul2(hi.y, ch.y), hmul2(lo.y, sh.y));
                    t[r][j][2] = hsub2(hmul2(lo.z, cl.z), hmul2(hi.z, sl.z)); t[r][j + 2][2] = hadd2(hmul2(hi.z, ch.z), hmul2(lo.z, sh.z));
                    t[r][j][3] = hsub2(hmul2(lo.w, cl.w), hmul2(hi.w, sl.w)); t[r][j + 2][3] = hadd2(hmul2(hi.w, ch.w), hmul2(lo.w, sh.w));
                }
            }
#pragma unroll
            for (int r = 0; r < 2; r++)
#pragma unroll
                for (int j = 0; j < 4; j++)
#pragma unroll
                    for (int i = 0; i < 4; i++)
                        q[4 * (2 * j + (i >> 1)) + r + 2 * (i & 1)] = prescale(odd ? t[r][j ^ 1][i] : t[r][j][i]);
            fence_regs(q);
        }
        auto hand_back = [&]() {
            if (SUMTC) {
                bar_sync(6 + wg, 128);
                write_ones(wg);
            }
            __syncwarp();
            if (lane < 2) mbar_arrive_cluster(rel_addr + 8 * (2 + wg));
        };
        if (!ONESLATE) hand_back();
        if ((warp & 3) == 0) TR(2 + wg);

        float s[64], o[kON];
        uint32_t pr[32];
        float ms0 = 0.f, ms1 = 0.f, l0 = 0.f, l1 = 0.f;
#pragma unroll
        for (int i = 0; i < kON; i++) o[i] = 0.f;

        const uint32_t sb4 = (sbase & 0x3FFFF) >> 4;
        const uint64_t dk0 = kDescK | sb4, dv0 = kDescV | (sb4 + (kSmemVOff >> 4));
        const uint32_t id_mine = __shfl_sync(0xffffffffu, 1 + wg, lane), id_other = __shfl_sync(0xffffffffu, 2 - wg, lane);
        const bool rel = lane < 2;

        if (wg == 1) bar_sync(2, 256);
        mbar_wait(bar_full, 0);
        if ((warp & 3) == 0) TR(16 + 48 * wg);
        WG_FENCE();
        gemm_qk(s, q, dk0);
        WG_COMMIT();
        if (ONESLATE) hand_back();
        wg_wait<0>();
        fence_regs(s);
        bar_arrive(id_other, 256);
        if (rel) mbar_arrive_cluster(rel_addr);
        if (MAXMODE != 2) {
            row_max(s, ms0, ms1);
            ms0 *= kScale; ms1 *= kScale;
        }
        exp_tile<!SUMTC, 0, 16, MAXMODE != 2>(s, ms0, ms1, l0, l1);
        pack_tile(pr, s);
        uint64_t nm0 = 0, nm1 = 0;
        if (MAXMODE == 1) {
            asm("mov.b64 %0, {%1,%1};" : "=l"(nm0) : "f"(-ms0));
            asm("mov.b64 %0, {%1,%1};" : "=l"(nm1) : "f"(-ms1));
        }
        auto preset = [&]() {
            if (MAXMODE == 1) {
#pragma unroll
                for (int i = 0; i < 32; i++) {
                    uint64_t d;
                    asm("mad.wide.u32 %0, %1, %2, %3;" : "=l"(d) : "r"(pr[i]), "r"(p.zero3), "l"((i & 1) ? nm1 : nm0));
                    asm("mov.b64 {%0,%1}, %2;" : "=f"(s[2 * i]), "=f"(s[2 * i + 1]) : "l"(d));
                }
            }
        };
        preset();

        const uint32_t never = p.zero;
        uint64_t dk = dk0, dv = dv0;
        auto step = [&](int j, int ks, int vs, uint32_t kpar, uint32_t vpar, uint32_t z) {
            mbar_wait(bar_full + 8 * ks, kpar);
            if (VEARLY) mbar_wait(bar_full + 16 + 8 * vs, vpar);
            bar_sync(id_mine, 256);
            if (TRACE_FULL && (warp & 3) == 0) TR(16 + 48 * wg + j);
            fence_regs(s); fence_regs(o); fence_regs(pr);
            WG_FENCE();
            gemm_qk<MAXMODE == 1>(s, q, dk + ks * (kTileBytes >> 4));
            WG_COMMIT();
            if (!VEARLY) {
                mbar_wait(bar_full + 16 + 8 * vs, vpar);
                WG_FENCE();
            }
            gemm_pv(o, pr, dv + vs * (kVSlotBytes >> 4));
            WG_COMMIT();
            bar_arrive(id_other, 256);
            wg_wait<1>();
            if ((TRACE_FULL || (ks == 1 && wg == 0)) && (warp & 3) == TRW) TR(32 + 48 * wg + j);
            fence_regs(s);
            if (rel) mbar_arrive_cluster(rel_addr + 8 * ks);
            exp_tile<!SUMTC, 0, ESPLIT, MAXMODE == 0>(s, ms0, ms1, l0, l1);
            sched_boundary(z);
            wg_wait<0>();
            if (TRACE_FULL && (warp & 3) == 0) TR(48 + 48 * wg + j);
            fence_regs(o); fence_regs(s);
            if (rel) mbar_arrive_cluster(rel_addr + 16 + 8 * vs);
            exp_tile<!SUMTC, ESPLIT, 16>(s, ms0, ms1, l0, l1);
            pack_tile(pr, s);
            preset();
        };
        step(1, 1, 0, 0, 0, p.zero2);
#pragma unroll 1
        for (int i = 1; i < 8; i++) {
            step(2 * i, 0, 1, i, i + 1, never);
            step(2 * i + 1, 1, 0, i, i, p.zero1);
            dk += never; dv += never;
        }
        asm volatile("barrier.cluster.arrive.relaxed.aligned;" ::: "memory");

        __nv_bfloat16* op = p.out + ((size_t)h * kS + qt * 128 + warp * 16 + g) * kD + 8 * c;
        if (wg == 0) bar_sync(1, 256);
        mbar_wait(bar_full + 24, 1);
        fence_regs(o); fence_regs(pr);
        WG_FENCE();
        uint4 v[8];
        gemm_pv(o, pr, dv0 + (kVSlotBytes >> 4));
        WG_COMMIT();
        if (!SUMTC) {
            l0 += __shfl_xor_sync(0xffffffffu, l0, 1); l1 += __shfl_xor_sync(0xffffffffu, l1, 1);
            l0 += __shfl_xor_sync(0xffffffffu, l0, 2); l1 += __shfl_xor_sync(0xffffffffu, l1, 2);
        }
        wg_wait<0>();
        if ((warp & 3) == 0) TR(4 + wg);
        fence_regs(o);
        if (SUMTC) { l0 = o[kON - 4]; l1 = o[kON - 2]; }
        store_cols<0, 4>(op, v, o, rcp(l0), rcp(l1));
        bool ok = all_finite(v, never);
        if ((warp & 3) == 0) TR(14 + wg);
        if ((warp & 3) == 0) { TR(6 + wg); TRG(8 + wg); }

        ok = ok && l0 <= 1.0995116e12f && l1 <= 1.0995116e12f;
        if (MAXMODE == 2) ok = ok && l0 >= 9.094947e-13f && l1 >= 9.094947e-13f;
        if (bar_red_or(3, 256, !ok && !HACK1)) {
            float m0 = -INFINITY, m1 = -INFINITY;
            l0 = 0.f; l1 = 0.f;
#pragma unroll
            for (int i = 0; i < kON; i++) o[i] = 0.f;
            const uint8_t* src = g_scratch + (size_t)h * kItems * kTileBytes;
#pragma unroll 1
            for (int j = 0; j < 16; j++) {
                if (threadIdx.x == 0) {
                    asm volatile("fence.proxy.async;" ::: "memory");
                    mbar_expect_tx(bar_fb, 2 * kTileBytes);
                    bulk_g2s(sbase, src + (size_t)(j == 0 ? 0 : 2 * j - 1) * kTileBytes, kTileBytes, bar_fb);
                    for (int gi = 0; gi < 16; gi++)
                        bulk_g2s(sbase + kSmemVOff + gi * kVGroup, src + (size_t)(2 * j + 2) * kTileBytes + gi * 2048, 2048, bar_fb);
                }
                mbar_wait(bar_fb, j & 1);
                fence_regs(s);
                WG_FENCE();
                gemm_qk(s, q, dk0);
                WG_COMMIT();
                wg_wait<0>();
                fence_regs(s);
                float a0, a1;
                row_max(s, a0, a1);
                a0 = fmaxf(a0, m0); a1 = fmaxf(a1, m1);
                const float al0 = ex2((m0 - a0) * kScale), al1 = ex2((m1 - a1) * kScale);
                m0 = a0; m1 = a1;
                l0 *= al0; l1 *= al1;
                exp_tile<!SUMTC, 0, 16>(s, m0 * kScale, m1 * kScale, l0, l1);
                pack_tile(pr, s);
#pragma unroll
                for (int n = 0; n < kON / 4; n++) { o[4 * n] *= al0; o[4 * n + 1] *= al0; o[4 * n + 2] *= al1; o[4 * n + 3] *= al1; }
                fence_regs(o); fence_regs(pr);
                WG_FENCE();
                gemm_pv(o, pr, dv0);
                WG_COMMIT();
                wg_wait<0>();
                fence_regs(o);
                bar_sync(3, 256);
            }
            if (SUMTC) {
                l0 = o[kON - 4]; l1 = o[kON - 2];
            } else {
                l0 += __shfl_xor_sync(0xffffffffu, l0, 1); l1 += __shfl_xor_sync(0xffffffffu, l1, 1);
                l0 += __shfl_xor_sync(0xffffffffu, l0, 2); l1 += __shfl_xor_sync(0xffffffffu, l1, 2);
            }
            store_cols<0, 4>(op, v, o, 1.f / l0, 1.f / l1);
        }
        asm volatile("barrier.cluster.wait.aligned;" ::: "memory");
    }
}

}

extern "C" void kernel_launch(void* const* d_in, const int* in_sizes, int n_in, void* d_out, int out_size) {
    (void)in_sizes; (void)n_in; (void)out_size;
    Params p;
    p.q = (const __nv_bfloat16*)d_in[0];
    p.qk = (const int*)d_in[1];
    p.k_scales = (const __nv_bfloat16*)d_in[2];
    p.k_zeros = (const __nv_bfloat16*)d_in[3];
    p.qv = (const int*)d_in[4];
    p.v_scales = (const __nv_bfloat16*)d_in[5];
    p.v_zeros = (const __nv_bfloat16*)d_in[6];
    p.q_cos = (const __nv_bfloat16*)d_in[7];
    p.q_sin = (const __nv_bfloat16*)d_in[8];
    p.k_cos = (const __nv_bfloat16*)d_in[9];
    p.k_sin = (const __nv_bfloat16*)d_in[10];
    p.out = (__nv_bfloat16*)d_out;
    p.zero = p.zero1 = p.zero2 = p.zero3 = 0;
    const uint32_t t_def[8] = {400, 900, 460, 5600, 400, 2700, 360, 4800};
    for (int i = 0; i < 8; i++) p.t[i] = t_def[i];
    p.u[0] = 2000; p.u[1] = 0; p.u[2] = p.u[3] = 0;
    static bool configured = false;
    if (!configured) {
        cudaFuncSetAttribute(attn_kernel, cudaFuncAttributeMaxDynamicSharedMemorySize, kSmemBytes);
        configured = true;
    }
    attn_kernel<<<kH * 16, 384, kSmemBytes>>>(p);
}
```

```cpp
#include <cuda_runtime.h>
#include <cuda_bf16.h>
#include <stdint.h>

namespace {

constexpr int kH = 8, kS = 2048, kD = 128;
constexpr int kItems = 33;
constexpr int kTileBytes = 32768;
constexpr int kVSlotBytes = 49152;
constexpr int kDqWarps = 3;
constexpr int kRawBytes = 12288;
constexpr int kSmemVOff = 2 * kTileBytes;
constexpr int kSmemRawOff = kSmemVOff + 2 * kVSlotBytes;
constexpr int kSmemOutOff = kSmemRawOff + kDqWarps * kRawBytes;
constexpr int kSmemScOff = kSmemOutOff + kDqWarps * 2048;
constexpr int kSmemBarOff = kSmemScOff + kDqWarps * 768;
constexpr int kSmemBytes = kSmemBarOff + 256 + 1024;
constexpr int kFlagStride = 64;
constexpr int kON = 68;
constexpr float kScale = 0.08838834764831845f * 1.4426950408889634f;
constexpr uint32_t kWaitLimit = 1u << 30;
#define ESPLIT 9
#define EQK 8

__device__ __align__(1024) uint8_t g_scratch[(size_t)kH * kItems * kTileBytes];
__device__ __align__(256) unsigned g_flags[kH * kItems * kFlagStride];
__device__ unsigned g_done;

#define TR(idx) do {} while (0)
#define TRG(idx) do {} while (0)
#define TRN(base, n) do {} while (0)
#define TRC(cond, idx) do {} while (0)

struct Params {
    const __nv_bfloat16* q;
    const int* qk;
    const __nv_bfloat16* k_scales;
    const __nv_bfloat16* k_zeros;
    const int* qv;
    const __nv_bfloat16* v_scales;
    const __nv_bfloat16* v_zeros;
    const __nv_bfloat16* q_cos;
    const __nv_bfloat16* q_sin;
    const __nv_bfloat16* k_cos;
    const __nv_bfloat16* k_sin;
    __nv_bfloat16* out;
    uint32_t zero[5];
    int t_v0, t_q, dt_q, t_next, dt_next, t_k2, gap_q, k_v1, t_poll, stagger, lag_q, catch_q;
};

__device__ __forceinline__ uint32_t smem_u32(const void* p) { return (uint32_t)__cvta_generic_to_shared(p); }
__device__ __forceinline__ uint32_t clock32() {
    uint32_t c;
    asm volatile("mov.u32 %0, %%clock;" : "=r"(c));
    return c;
}
__device__ __forceinline__ void wait_until(uint32_t t0, int t) {
    while ((int)(clock32() - t0) < t) {}
    __syncwarp();
}
__device__ __forceinline__ bool elect() {
    uint32_t r;
    asm volatile("{\n.reg .pred p;\nelect.sync _|p, 0xffffffff;\nselp.u32 %0, 1, 0, p;\n}\n" : "=r"(r));
    return r != 0;
}
__device__ __forceinline__ void mbar_init(uint32_t bar, uint32_t count) {
    asm volatile("mbarrier.init.shared::cta.b64 [%0], %1;" ::"r"(bar), "r"(count) : "memory");
}
__device__ __forceinline__ void mbar_expect_tx(uint32_t bar, uint32_t bytes) {
    asm volatile("mbarrier.arrive.expect_tx.shared::cta.b64 _, [%0], %1;" ::"r"(bar), "r"(bytes) : "memory");
}
__device__ __forceinline__ bool mbar_try(uint32_t bar, uint32_t parity) {
    uint32_t ok;
    asm volatile(
        "{\n.reg .pred p;\n"
        "mbarrier.try_wait.parity.shared::cta.b64 p, [%1], %2;\n"
        "selp.u32 %0, 1, 0, p;\n}\n"
        : "=r"(ok)
        : "r"(bar), "r"(parity)
        : "memory");
    return ok != 0;
}
__device__ __forceinline__ void mbar_wait(uint32_t bar, uint32_t parity) {
    if (mbar_try(bar, parity)) return;
    const uint32_t t0 = clock32();
    while (!mbar_try(bar, parity)) {
        if (clock32() - t0 > kWaitLimit) break;
    }
}
__device__ __forceinline__ void mbar_wait_idle(uint32_t bar, uint32_t parity) {
    if (mbar_try(bar, parity)) return;
    const uint32_t t0 = clock32();
    uint32_t ok;
    do {
        asm volatile(
            "{\n.reg .pred p;\n"
            "mbarrier.try_wait.parity.shared::cta.b64 p, [%1], %2, 20000;\n"
            "selp.u32 %0, 1, 0, p;\n}\n"
            : "=r"(ok)
            : "r"(bar), "r"(parity)
            : "memory");
    } while (!ok && clock32() - t0 <= kWaitLimit);
    __syncwarp();
}
__device__ __forceinline__ void mbar_arrive_cluster(uint32_t cluster_addr) {
    asm volatile("mbarrier.arrive.shared::cluster.b64 _, [%0];" ::"r"(cluster_addr) : "memory");
}
__device__ __forceinline__ uint32_t mapa(uint32_t addr, uint32_t rank) {
    uint32_t r;
    asm("mapa.shared::cluster.u32 %0, %1, %2;" : "=r"(r) : "r"(addr), "r"(rank));
    return r;
}
__device__ __forceinline__ void bulk_g2s(uint32_t dst, const void* src, uint32_t bytes, uint32_t bar) {
    asm volatile("cp.async.bulk.shared::cluster.global.mbarrier::complete_tx::bytes [%0], [%1], %2, [%3];" ::"r"(dst),
                 "l"(src), "r"(bytes), "r"(bar)
                 : "memory");
}
__device__ __forceinline__ void bulk_g2s_mc(uint32_t dst, const void* src, uint32_t bytes, uint32_t bar, uint16_t mask) {
    asm volatile(
        "cp.async.bulk.shared::cluster.global.mbarrier::complete_tx::bytes.multicast::cluster [%0], [%1], %2, [%3], %4;" ::"r"(dst),
        "l"(src), "r"(bytes), "r"(bar), "h"(mask)
        : "memory");
}
__device__ __forceinline__ void cp_async_4k(uint32_t dst, const void* src) {
#pragma unroll
    for (int i = 0; i < 8; i++)
        asm volatile("cp.async.cg.shared.global [%0], [%1], 16;" ::"r"(dst + i * 512), "l"((const uint8_t*)src + i * 512) : "memory");
}
__device__ __forceinline__ void bar_sync(int id, int n) { asm volatile("bar.sync %0, %1;" ::"r"(id), "r"(n) : "memory"); }
__device__ __forceinline__ void bar_arrive(int id, int n) { asm volatile("bar.arrive %0, %1;" ::"r"(id), "r"(n) : "memory"); }
__device__ __forceinline__ bool bar_red_or(int id, int n, bool v) {
    uint32_t r;
    asm volatile(
        "{\n.reg .pred p, q;\nsetp.ne.u32 q, %3, 0;\n"
        "bar.red.or.pred p, %1, %2, q;\nselp.u32 %0, 1, 0, p;\n}\n"
        : "=r"(r)
        : "r"(id), "r"(n), "r"((uint32_t)v)
        : "memory");
    return r != 0;
}
__device__ __forceinline__ void sched_boundary(uint32_t zero) {
    asm volatile("{\n.reg .pred p;\nsetp.ne.u32 p, %0, 0;\n@p exit;\n}\n" ::"r"(zero) : "memory");
}
__device__ __forceinline__ float ex2(float x) {
    float y;
    asm("ex2.approx.ftz.f32 %0, %1;" : "=f"(y) : "f"(x));
    return y;
}
__device__ __forceinline__ float rcp(float x) {
    float y;
    asm("rcp.approx.ftz.f32 %0, %1;" : "=f"(y) : "f"(x));
    return y;
}
__device__ __forceinline__ uint32_t pack_bf16(float lo, float hi) {
    uint32_t r;
    asm("cvt.rn.bf16x2.f32 %0, %1, %2;" : "=r"(r) : "f"(hi), "f"(lo));
    return r;
}
__device__ __forceinline__ uint32_t hmul2(uint32_t a, uint32_t b) {
    uint32_t r;
    asm("mul.rn.bf16x2 %0, %1, %2;" : "=r"(r) : "r"(a), "r"(b));
    return r;
}
__device__ __forceinline__ uint32_t hadd2(uint32_t a, uint32_t b) {
    uint32_t r;
    asm("add.rn.bf16x2 %0, %1, %2;" : "=r"(r) : "r"(a), "r"(b));
    return r;
}
__device__ __forceinline__ uint32_t hsub2(uint32_t a, uint32_t b) {
    uint32_t r;
    asm("sub.rn.bf16x2 %0, %1, %2;" : "=r"(r) : "r"(a), "r"(b));
    return r;
}
__device__ __forceinline__ uint32_t hfma2(uint32_t a, uint32_t b, uint32_t c) {
    uint32_t r;
    asm("fma.rn.bf16x2 %0, %1, %2, %3;" : "=r"(r) : "r"(a), "r"(b), "r"(c));
    return r;
}
__device__ __forceinline__ uint4 lds128(uint32_t a) {
    uint4 v;
    asm volatile("ld.shared.v4.u32 {%0,%1,%2,%3}, [%4];" : "=r"(v.x), "=r"(v.y), "=r"(v.z), "=r"(v.w) : "r"(a));
    return v;
}
__device__ __forceinline__ uint2 lds64(uint32_t a) {
    uint2 v;
    asm volatile("ld.shared.v2.u32 {%0,%1}, [%2];" : "=r"(v.x), "=r"(v.y) : "r"(a));
    return v;
}
__device__ __forceinline__ uint32_t lds32(uint32_t a) {
    uint32_t v;
    asm volatile("ld.shared.u32 %0, [%1];" : "=r"(v) : "r"(a));
    return v;
}
__device__ __forceinline__ void sts32(uint32_t a, uint32_t v) { asm volatile("st.shared.u32 [%0], %1;" ::"r"(a), "r"(v) : "memory"); }
__device__ __forceinline__ uint4 ldg128(const void* p) {
    uint4 v;
    asm volatile("ld.global.nc.L1::no_allocate.v4.u32 {%0,%1,%2,%3}, [%4];" : "=r"(v.x), "=r"(v.y), "=r"(v.z), "=r"(v.w) : "l"(p) : "memory");
    return v;
}
__device__ __forceinline__ uint2 ldg64(const void* p) {
    uint2 v;
    asm volatile("ld.global.nc.L1::no_allocate.v2.u32 {%0,%1}, [%2];" : "=r"(v.x), "=r"(v.y) : "l"(p) : "memory");
    return v;
}
__device__ __forceinline__ uint32_t ldg32(const void* p) {
    uint32_t v;
    asm volatile("ld.global.nc.L1::no_allocate.u32 %0, [%1];" : "=r"(v) : "l"(p) : "memory");
    return v;
}
__device__ __forceinline__ uint32_t ld_gpu(const void* p) {
    uint32_t v;
    asm volatile("ld.relaxed.gpu.global.u32 %0, [%1];" : "=r"(v) : "l"(p) : "memory");
    return v;
}
__device__ __forceinline__ void red_gpu(unsigned* p, uint32_t v) {
    asm volatile("red.relaxed.gpu.global.add.u32 [%0], %1;" ::"l"(p), "r"(v) : "memory");
}

#define WG_FENCE() asm volatile("wgmma.fence.sync.aligned;" ::: "memory")
#define WG_COMMIT() asm volatile("wgmma.commit_group.sync.aligned;" ::: "memory")
template <int N>
__device__ __forceinline__ void wg_wait() {
    asm volatile("wgmma.wait_group.sync.aligned %0;" ::"n"(N) : "memory");
}
template <int ACC>
__device__ __forceinline__ void wgmma_qk(float (&d)[64], uint32_t a0, uint32_t a1, uint32_t a2, uint32_t a3, uint64_t db) {
    asm volatile(
        "{\n.reg .pred p;\nsetp.ne.b32 p, %69, 0;\n"
        "wgmma.mma_async.sync.aligned.m64n128k16.f32.bf16.bf16 "
        "{%0,%1,%2,%3,%4,%5,%6,%7,%8,%9,%10,%11,%12,%13,%14,%15,%16,%17,%18,%19,%20,%21,%22,%23,"
        "%24,%25,%26,%27,%28,%29,%30,%31,%32,%33,%34,%35,%36,%37,%38,%39,%40,%41,%42,%43,%44,%45,%46,%47,"
        "%48,%49,%50,%51,%52,%53,%54,%55,%56,%57,%58,%59,%60,%61,%62,%63}, {%64,%65,%66,%67}, %68, p, 1, 1, 0;\n}\n"
        : "+f"(d[0]), "+f"(d[1]), "+f"(d[2]), "+f"(d[3]), "+f"(d[4]), "+f"(d[5]), "+f"(d[6]), "+f"(d[7]),
          "+f"(d[8]), "+f"(d[9]), "+f"(d[10]), "+f"(d[11]), "+f"(d[12]), "+f"(d[13]), "+f"(d[14]), "+f"(d[15]),
          "+f"(d[16]), "+f"(d[17]), "+f"(d[18]), "+f"(d[19]), "+f"(d[20]), "+f"(d[21]), "+f"(d[22]), "+f"(d[23]),
          "+f"(d[24]), "+f"(d[25]), "+f"(d[26]), "+f"(d[27]), "+f"(d[28]), "+f"(d[29]), "+f"(d[30]), "+f"(d[31]),
          "+f"(d[32]), "+f"(d[33]), "+f"(d[34]), "+f"(d[35]), "+f"(d[36]), "+f"(d[37]), "+f"(d[38]), "+f"(d[39]),
          "+f"(d[40]), "+f"(d[41]), "+f"(d[42]), "+f"(d[43]), "+f"(d[44]), "+f"(d[45]), "+f"(d[46]), "+f"(d[47]),
          "+f"(d[48]), "+f"(d[49]), "+f"(d[50]), "+f"(d[51]), "+f"(d[52]), "+f"(d[53]), "+f"(d[54]), "+f"(d[55]),
          "+f"(d[56]), "+f"(d[57]), "+f"(d[58]), "+f"(d[59]), "+f"(d[60]), "+f"(d[61]), "+f"(d[62]), "+f"(d[63])
        : "r"(a0), "r"(a1), "r"(a2), "r"(a3), "l"(db), "n"(ACC));
}
__device__ __forceinline__ void wgmma_pv(float (&d)[kON], uint32_t a0, uint32_t a1, uint32_t a2, uint32_t a3, uint64_t db) {
    asm volatile(
        "wgmma.mma_async.sync.aligned.m64n136k16.f32.bf16.bf16 "
        "{%0,%1,%2,%3,%4,%5,%6,%7,%8,%9,%10,%11,%12,%13,%14,%15,%16,%17,%18,%19,%20,%21,%22,%23,"
        "%24,%25,%26,%27,%28,%29,%30,%31,%32,%33,%34,%35,%36,%37,%38,%39,%40,%41,%42,%43,%44,%45,%46,%47,"
        "%48,%49,%50,%51,%52,%53,%54,%55,%56,%57,%58,%59,%60,%61,%62,%63,%64,%65,%66,%67}, {%68,%69,%70,%71}, %72, 1, 1, 1, 1;\n"
        : "+f"(d[0]), "+f"(d[1]), "+f"(d[2]), "+f"(d[3]), "+f"(d[4]), "+f"(d[5]), "+f"(d[6]), "+f"(d[7]),
          "+f"(d[8]), "+f"(d[9]), "+f"(d[10]), "+f"(d[11]), "+f"(d[12]), "+f"(d[13]), "+f"(d[14]), "+f"(d[15]),
          "+f"(d[16]), "+f"(d[17]), "+f"(d[18]), "+f"(d[19]), "+f"(d[20]), "+f"(d[21]), "+f"(d[22]), "+f"(d[23]),
          "+f"(d[24]), "+f"(d[25]), "+f"(d[26]), "+f"(d[27]), "+f"(d[28]), "+f"(d[29]), "+f"(d[30]), "+f"(d[31]),
          "+f"(d[32]), "+f"(d[33]), "+f"(d[34]), "+f"(d[35]), "+f"(d[36]), "+f"(d[37]), "+f"(d[38]), "+f"(d[39]),
          "+f"(d[40]), "+f"(d[41]), "+f"(d[42]), "+f"(d[43]), "+f"(d[44]), "+f"(d[45]), "+f"(d[46]), "+f"(d[47]),
          "+f"(d[48]), "+f"(d[49]), "+f"(d[50]), "+f"(d[51]), "+f"(d[52]), "+f"(d[53]), "+f"(d[54]), "+f"(d[55]),
          "+f"(d[56]), "+f"(d[57]), "+f"(d[58]), "+f"(d[59]), "+f"(d[60]), "+f"(d[61]), "+f"(d[62]), "+f"(d[63]),
          "+f"(d[64]), "+f"(d[65]), "+f"(d[66]), "+f"(d[67])
        : "r"(a0), "r"(a1), "r"(a2), "r"(a3), "l"(db));
}
template <int N>
__device__ __forceinline__ void fence_regs(float (&d)[N]) {
#pragma unroll
    for (int i = 0; i < N; i++) asm volatile("" : "+f"(d[i])::"memory");
}
__device__ __forceinline__ void fence_regs(uint32_t (&d)[32]) {
#pragma unroll
    for (int i = 0; i < 32; i++) asm volatile("" : "+r"(d[i])::"memory");
}
constexpr uint64_t kDescK = (uint64_t(1) << 62) | (uint64_t(1024 >> 4) << 32) | (uint64_t(1) << 16);
constexpr uint64_t kDescV = (uint64_t(1) << 62) | (uint64_t(1024 >> 4) << 32) | (uint64_t(16384 >> 4) << 16);

__device__ __forceinline__ void gemm_qk(float (&s)[64], const uint32_t (&q)[32], uint64_t d) {
    wgmma_qk<0>(s, q[0], q[1], q[2], q[3], d);
#pragma unroll
    for (int kk = 1; kk < 8; kk++)
        wgmma_qk<1>(s, q[4 * kk], q[4 * kk + 1], q[4 * kk + 2], q[4 * kk + 3], d + (((kk >> 2) * 16384 + (kk & 3) * 32) >> 4));
}
__device__ __forceinline__ void gemm_pv(float (&o)[kON], const uint32_t (&p)[32], uint64_t d) {
#pragma unroll
    for (int kk = 0; kk < 8; kk++) wgmma_pv(o, p[4 * kk], p[4 * kk + 1], p[4 * kk + 2], p[4 * kk + 3], d + ((kk * 2048) >> 4));
}

__device__ __forceinline__ void dequant4(uint32_t (&v)[4], uint32_t sc, uint32_t zp) {
    const uint32_t s0 = __byte_perm(sc, 0, 0x1010), s1 = __byte_perm(sc, 0, 0x3232);
    const uint32_t z0 = __byte_perm(zp, 0, 0x1010), z1 = __byte_perm(zp, 0, 0x3232);
    v[0] = hmul2(hsub2(v[0], z0), s0); v[1] = hmul2(hsub2(v[1], z0), s0);
    v[2] = hmul2(hsub2(v[2], z1), s1); v[3] = hmul2(hsub2(v[3], z1), s1);
}
__device__ __forceinline__ void to_bf16(uint32_t (&v)[4], const uint4& lo, const uint4& hi) {
    v[0] = pack_bf16((float)(int)lo.x, (float)(int)lo.y); v[1] = pack_bf16((float)(int)lo.z, (float)(int)lo.w);
    v[2] = pack_bf16((float)(int)hi.x, (float)(int)hi.y); v[3] = pack_bf16((float)(int)hi.z, (float)(int)hi.w);
}
__device__ __forceinline__ void rope4(uint32_t (&v)[4], const uint2& cl, const uint2& ch, const uint2& sl, const uint2& sh) {
    const uint32_t r0 = hsub2(hmul2(v[0], cl.x), hmul2(v[2], sl.x)), r1 = hsub2(hmul2(v[1], cl.y), hmul2(v[3], sl.y));
    const uint32_t r2 = hadd2(hmul2(v[2], ch.x), hmul2(v[0], sh.x)), r3 = hadd2(hmul2(v[3], ch.y), hmul2(v[1], sh.y));
    v[0] = r0; v[1] = r1; v[2] = r2; v[3] = r3;
}

template <bool IS_V>
__device__ __forceinline__ void dequant_slice(uint32_t ia, uint32_t ca, uint32_t oa, uint32_t sc, uint32_t zp) {
    uint4 lo = lds128(ia), hi = lds128(ia + 256);
#pragma unroll
    for (int it = 0; it < 4; it++) {
        uint2 cl, ch, sl, sh;
        if (!IS_V) {
            const uint32_t a = ca ^ ((it >> 1) * 64 + (it & 1) * 8);
            cl = lds64(a); sl = lds64(a + 2048); ch = lds64(a + 128); sh = lds64(a + 2048 + 128);
        }
        uint32_t v[4];
        to_bf16(v, lo, hi);
        if (it < 3) {
            const uint32_t a = ia ^ (((it + 1) >> 1) * 128 + ((it + 1) & 1) * 16);
            lo = lds128(a); hi = lds128(a + 256);
        }
        dequant4(v, sc, zp);
        if (!IS_V) rope4(v, cl, ch, sl, sh);
        const uint32_t o0 = oa ^ (it << 5), o1 = oa ^ ((it << 5) | 16);
        sts32(o0, v[0]); sts32(o1, v[1]); sts32(o0 + 1024, v[2]); sts32(o1 + 1024, v[3]);
    }
}

struct RowsIn { uint4 lo, hi; uint2 cl, ch, sl, sh; uint32_t sc, zp; };
template <bool IS_V>
__device__ __forceinline__ void rows_load(RowsIn& x, const Params& p, int h, int row, int mp) {
    const int hr = h * kS + row;
    const int* ints = (IS_V ? p.qv : p.qk) + hr * kD + 4 * mp;
    x.lo = ldg128(ints); x.hi = ldg128(ints + 64);
    if (!IS_V) {
        x.cl = ldg64(p.k_cos + row * kD + 4 * mp); x.ch = ldg64(p.k_cos + row * kD + 64 + 4 * mp);
        x.sl = ldg64(p.k_sin + row * kD + 4 * mp); x.sh = ldg64(p.k_sin + row * kD + 64 + 4 * mp);
    }
    x.sc = ldg32((IS_V ? p.v_scales : p.k_scales) + hr * 2); x.zp = ldg32((IS_V ? p.v_zeros : p.k_zeros) + hr * 2);
}
template <bool IS_V>
__device__ __forceinline__ uint8_t* rows_store(const RowsIn& a, uint8_t* slice, int r, int mp) {
    const int j = mp >> 3, c = (mp >> 1) & 3, b = mp & 1;
    uint32_t v[4];
    to_bf16(v, a.lo, a.hi);
    dequant4(v, a.sc, a.zp);
    if (!IS_V) rope4(v, a.cl, a.ch, a.sl, a.sh);
    const bool c0 = c & 1, c1 = c & 2;
    uint32_t x = __shfl_xor_sync(0xffffffffu, c0 ? v[0] : v[1], 2), y = __shfl_xor_sync(0xffffffffu, c0 ? v[2] : v[3], 2);
    const uint32_t a0 = c0 ? x : v[0], a1 = c0 ? v[1] : x, a2 = c0 ? y : v[2], a3 = c0 ? v[3] : y;
    x = __shfl_xor_sync(0xffffffffu, c1 ? a0 : a2, 4); y = __shfl_xor_sync(0xffffffffu, c1 ? a1 : a3, 4);
    uint8_t* dst = slice + (c >> 1) * 16384 + r * 128 + (((4 * j + 2 * b + (c & 1)) ^ r) << 4);
    *reinterpret_cast<uint4*>(dst) = make_uint4(c1 ? x : a0, c1 ? y : a1, c1 ? a2 : x, c1 ? a3 : y);
    return dst;
}

__global__ void __launch_bounds__(128) prefill_kernel(const __grid_constant__ Params p) {
    const int slice = blockIdx.x & 15, h = (blockIdx.x >> 4) & 7, n = blockIdx.x >> 7;
    if (n == kItems - 2) return;
    const int r = threadIdx.x >> 4, mp = threadIdx.x & 15;
    const bool is_v = n != 0 && !(n & 1);
    const int row = (is_v ? (n >> 1) - 1 : (n + 1) >> 1) * 128 + slice * 8 + r;
    uint8_t* dst = g_scratch + (size_t)(h * kItems + n) * kTileBytes + slice * 1024;
    RowsIn x;
    if (is_v) { rows_load<true>(x, p, h, row, mp); rows_store<true>(x, dst, r, mp); }
    else { rows_load<false>(x, p, h, row, mp); rows_store<false>(x, dst, r, mp); }
    if (threadIdx.x == 0 && slice == 0) g_flags[(h * kItems + n) * kFlagStride] = 16;
}

template <int N0, int N1>
__device__ __forceinline__ void exp_tile(float (&s)[64], float ms0, float ms1) {
    if (N0 == 0) {
#pragma unroll
        for (int i = 0; i < 64; i++) s[i] = fmaf(s[i], kScale, (i & 2) ? -ms1 : -ms0);
    }
#pragma unroll
    for (int i = 4 * N0; i < 4 * N1; i++) s[i] = ex2(s[i]);
}
__device__ __forceinline__ void row_max(const float (&s)[64], float& m0, float& m1) {
    float a0 = fmaxf(s[0], s[1]), a1 = fmaxf(s[2], s[3]), b0 = fmaxf(s[4], s[5]), b1 = fmaxf(s[6], s[7]);
#pragma unroll
    for (int n = 2; n < 16; n += 2) {
        a0 = fmaxf(a0, fmaxf(s[4 * n], s[4 * n + 1])); a1 = fmaxf(a1, fmaxf(s[4 * n + 2], s[4 * n + 3]));
        b0 = fmaxf(b0, fmaxf(s[4 * n + 4], s[4 * n + 5])); b1 = fmaxf(b1, fmaxf(s[4 * n + 6], s[4 * n + 7]));
    }
    m0 = fmaxf(a0, b0); m1 = fmaxf(a1, b1);
    m0 = fmaxf(m0, __shfl_xor_sync(0xffffffffu, m0, 1)); m1 = fmaxf(m1, __shfl_xor_sync(0xffffffffu, m1, 1));
    m0 = fmaxf(m0, __shfl_xor_sync(0xffffffffu, m0, 2)); m1 = fmaxf(m1, __shfl_xor_sync(0xffffffffu, m1, 2));
}
__device__ __forceinline__ void pack_tile(uint32_t (&pr)[32], const float (&s)[64]) {
#pragma unroll
    for (int i = 0; i < 32; i++) pr[i] = pack_bf16(s[2 * i], s[2 * i + 1]);
}
__device__ __forceinline__ bool store_rows(__nv_bfloat16* op, const float (&o)[kON], float i0, float i1, uint32_t zero) {
    uint4 v[8];
#pragma unroll
    for (int j = 0; j < 4; j++) {
        uint4 &v0 = v[2 * j], &v1 = v[2 * j + 1];
        v0.x = pack_bf16(o[16 * j] * i0, o[16 * j + 1] * i0);       v0.y = pack_bf16(o[16 * j + 4] * i0, o[16 * j + 5] * i0);
        v0.z = pack_bf16(o[16 * j + 8] * i0, o[16 * j + 9] * i0);   v0.w = pack_bf16(o[16 * j + 12] * i0, o[16 * j + 13] * i0);
        *reinterpret_cast<uint4*>(op + 32 * j) = v0;
        v1.x = pack_bf16(o[16 * j + 2] * i1, o[16 * j + 3] * i1);   v1.y = pack_bf16(o[16 * j + 6] * i1, o[16 * j + 7] * i1);
        v1.z = pack_bf16(o[16 * j + 10] * i1, o[16 * j + 11] * i1); v1.w = pack_bf16(o[16 * j + 14] * i1, o[16 * j + 15] * i1);
        *reinterpret_cast<uint4*>(op + 8 * kD + 32 * j) = v1;
    }
    uint32_t a[4] = {0, 0, 0, 0};
#pragma unroll
    for (int j = 0; j < 8; j++) {
        a[0] = hfma2(v[j].x, zero, a[0]); a[1] = hfma2(v[j].y, zero, a[1]);
        a[2] = hfma2(v[j].z, zero, a[2]); a[3] = hfma2(v[j].w, zero, a[3]);
    }
    return ((a[0] | a[1] | a[2] | a[3]) & 0x7fff7fffu) == 0;
}

template <bool B> struct Tag { static constexpr bool value = B; };

__global__ void __cluster_dims__(2, 1, 1) __launch_bounds__(384, 1) attn_kernel(const __grid_constant__ Params p) {
    extern __shared__ uint8_t smem_raw[];
    const uint32_t sbase = (smem_u32(smem_raw) + 1023) & ~1023u;
    const uint32_t bar_full = sbase + kSmemBarOff;
    const uint32_t bar_empty = bar_full + 32;
    const uint32_t bar_raw = bar_empty + 32;
    const uint32_t bar_q = bar_raw + 16 * kDqWarps;
    const uint32_t bar_fb = bar_q + 64;

    const int warp = __shfl_sync(0xffffffffu, threadIdx.x >> 5, 0), lane = threadIdx.x & 31;
    const int h = blockIdx.x >> 4, qt = blockIdx.x & 15;

    if (warp >= 8) {
        asm volatile("setmaxnreg.dec.sync.aligned.u32 56;");
        if (warp == 8) {
            const uint32_t t0 = clock32();
            TR(0); TRG(1);
            if (elect()) {
                for (int i = 0; i < 4; i++) {
                    mbar_init(bar_full + 8 * i, 1);
                    mbar_init(bar_empty + 8 * i, 16);
                }
                mbar_init(bar_fb, 1);
                asm volatile("fence.mbarrier_init.release.cluster;" ::: "memory");
            }
            __syncwarp();
            asm volatile("barrier.cluster.arrive.relaxed.aligned;" ::: "memory");
            asm volatile("barrier.cluster.wait.acquire.aligned;" ::: "memory");
            const uint32_t rank = blockIdx.x & 1;
            const uint8_t* src = g_scratch + (size_t)h * kItems * kTileBytes + rank * (kTileBytes / 2);
            const unsigned* fp = g_flags + (h * kItems + lane) * kFlagStride;
            uint32_t ready = 0, parity = 3;
            wait_until(t0, p.t_poll);
#pragma unroll 1
            for (int n = 0; n < kItems; n++, ready >>= 1, src += kTileBytes, fp += kFlagStride) {
                if (n == kItems - 2) continue;
                const bool mine = lane < 8 && n + lane < kItems;
                if (!(ready & 1)) {
                    const uint32_t t1 = clock32();
                    do {
                        ready = __ballot_sync(0xffffffffu, mine && ld_gpu(fp) >= 16);
                    } while (!(ready & 1) && !__any_sync(0xffffffffu, clock32() - t1 > kWaitLimit));
                    asm volatile("fence.acquire.gpu;" ::: "memory");
                }
                TRN(128, n);
                const bool is_v = n != 0 && !(n & 1);
                const int odd = (((n + 1) >> 1) & 1) ^ (is_v ? 1 : 0);
                const int slot = (is_v ? 2 : 0) + odd;
                const bool peek = !(ready & 2);
                uint32_t ahead = 0;
                if (peek && mine) ahead = ld_gpu(fp);
                mbar_wait_idle(bar_empty + 8 * slot, (parity >> slot) & 1);
                TRN(160, n);
                if (elect()) {
                    mbar_expect_tx(bar_full + 8 * slot, kTileBytes);
                    const uint32_t dst = sbase + (is_v ? kSmemVOff + odd * kVSlotBytes : odd * kTileBytes);
                    bulk_g2s_mc(dst + rank * (kTileBytes / 2), src, kTileBytes / 2, bar_full + 8 * slot, (uint16_t)3);
                }
                parity ^= 1u << slot;
                if (peek) {
                    ready = __ballot_sync(0xffffffffu, ahead >= 16);
                    asm volatile("fence.acquire.gpu;" ::: "memory");
                }
            }
            uint32_t ticket = 0;
            if (lane == 0) ticket = atomicAdd(&g_done, 1u);
            if (__shfl_sync(0xffffffffu, ticket, 0) == gridDim.x - 1) {
                for (int i = lane; i < kH * kItems; i += 32) g_flags[i * kFlagStride] = 0;
                if (lane == 0) g_done = 0;
            }
        } else {
            const int w = warp - 9;
            const uint32_t t0 = clock32() + p.stagger * h;
            const int first = w == 0 ? 2 : 5 - w;
            const int last = first == 4 ? 28 : kItems - 1;
            const uint32_t my_bar = bar_raw + 16 * w;
            const uint32_t my_raw = sbase + kSmemRawOff + w * kRawBytes;
            const uint32_t my_out = sbase + kSmemOutOff + w * 2048;
            const uint32_t my_sc = sbase + kSmemScOff + w * 768;
            auto fetch = [&](int n, auto tag) {
                constexpr bool V = decltype(tag)::value;
                const int row0 = (V ? (n >> 1) - 1 : (n + 1) >> 1) * 128 + qt * 8;
                if (elect()) {
                    if (V) {
                        mbar_expect_tx(my_bar + 8, 4096);
                        bulk_g2s(my_raw + 8192, p.qv + (h * kS + row0) * kD, 4096, my_bar + 8);
                    } else {
                        mbar_expect_tx(my_bar, 8192);
                        bulk_g2s(my_raw, p.qk + (h * kS + row0) * kD, 4096, my_bar);
                        bulk_g2s(my_raw + 4096, p.k_cos + row0 * kD, 2048, my_bar);
                        bulk_g2s(my_raw + 6144, p.k_sin + row0 * kD, 2048, my_bar);
                    }
                }
            };
            auto fetch_scales = [&](int k) {
                const int n = first + 3 * k;
                const int hr = h * kS + ((n & 1) ? (n + 1) >> 1 : (n >> 1) - 1) * 128 + qt * 8 + (lane & 7);
                const __nv_bfloat16* base = (n & 1) ? ((lane & 8) ? p.k_zeros : p.k_scales) : ((lane & 8) ? p.v_zeros : p.v_scales);
                if (n <= last) asm volatile("cp.async.ca.shared.global [%0], [%1], 4;" ::"r"(my_sc + k * 64 + (lane & 15) * 4), "l"(base + hr * 2) : "memory");
            };
            if (elect()) {
                mbar_init(my_bar, 1); mbar_init(my_bar + 8, 1);
                if (w == 1) for (int i = 0; i < 8; i++) mbar_init(bar_q + 8 * i, 32);
                asm volatile("fence.mbarrier_init.release.cluster;" ::: "memory");
            }
            __syncwarp();
            asm volatile("barrier.cluster.arrive.relaxed.aligned;" ::: "memory");
            fetch_scales(lane >> 4);
            asm volatile("cp.async.commit_group;" ::: "memory");
            if (w == 1) {
#pragma unroll 1
                for (int k = 0; k < 8; k++) {
                    const int row = qt * 128 + k * 16;
                    const uint32_t d = sbase + kSmemVOff + (k >> 2) * kVSlotBytes + (k & 3) * 4096 + ((lane * 16) ^ ((lane & 16) << 2));
                    wait_until(t0, p.t_q + h * p.lag_q + k * (p.dt_q - h * p.catch_q) + (k >> 2) * p.gap_q);
                    cp_async_4k(d, p.q + (h * kS + row) * kD + lane * 8);
                    cp_async_4k(d + 16384, p.q_cos + row * kD + lane * 8);
                    cp_async_4k(d + 32768, p.q_sin + row * kD + lane * 8);
                    asm volatile("cp.async.mbarrier.arrive.noinc.shared::cta.b64 [%0];" ::"r"(bar_q + 8 * k) : "memory");
                    if (k == p.k_v1) fetch(4, Tag<true>{});
                }
                TR(10);
            } else {
                wait_until(t0, w == 0 ? p.t_v0 : p.t_k2);
                if (w == 0) fetch(2, Tag<true>{}); else fetch(3, Tag<false>{});
            }
            const int r = lane >> 2, c = lane & 3, x = r & 3;
            const uint32_t ia = my_raw + r * 512 + c * 32 + (x >> 1) * 128 + (x & 1) * 16;
            const uint32_t ca = my_raw + 4096 + r * 256 + c * 16 + (x >> 1) * 64 + (x & 1) * 8;
            const uint32_t oa = my_out + r * 128 + c * 4 + (((2 * x) ^ r) << 4);
            const int back = (lane & 16) * 1024 + (lane & 15) * 64 - lane * 16;
            uint8_t* dst = g_scratch + (size_t)(h * kItems + first) * kTileBytes + qt * 1024 + lane * 16;
            uint32_t sa = my_sc + r * 4;
            auto convert = [&](int n, auto tag) {
                constexpr bool V = decltype(tag)::value;
                dequant_slice<V>(ia + (V ? 8192 : 0), ca, oa, lds32(sa), lds32(sa + 32));
                __syncwarp();
                const uint4 v0 = lds128(my_out + lane * 16), v1 = lds128(my_out + 512 + lane * 16);
                const uint4 v2 = lds128(my_out + 1024 + lane * 16), v3 = lds128(my_out + 1536 + lane * 16);
                uint4* d = reinterpret_cast<uint4*>(dst);
                d[0] = v0; d[32] = v1; d[1024] = v2; d[1056] = v3;
                TRN(256, n);
                return ld_gpu(dst + back);
            };
            auto publish = [&](int n, uint32_t seen) {
                const uint32_t one = 1u + (__reduce_or_sync(0xffffffffu, seen) & p.zero[0]);
                if (elect()) red_gpu(g_flags + (h * kItems + n) * kFlagStride, one);
                TRN(224, n);
                dst += (size_t)kDqWarps * kTileBytes;
                sa += 64;
            };
            auto round0 = [&](auto tag) {
                constexpr bool V = decltype(tag)::value;
                asm volatile("cp.async.wait_group 0;" ::: "memory");
                mbar_wait_idle(my_bar + (V ? 8 : 0), 0);
                __syncwarp();
                TRN(192, first);
                const uint32_t seen = convert(first, tag);
                const int due = p.t_next + (first - 2) * p.dt_next;
                const bool soon = __any_sync(0xffffffffu, (int)(clock32() - t0) + 800 >= due);
                if (!soon) publish(first, seen);
                wait_until(t0, due);
                fetch(first + kDqWarps, Tag<!V>{});
                if (soon) publish(first, seen);
            };
            if (first & 1) round0(Tag<false>{}); else round0(Tag<true>{});
#pragma unroll 1
            for (int k = 2; k < 12; k += 2) fetch_scales(k + (lane >> 4));
            asm volatile("cp.async.commit_group;" ::: "memory");
            uint32_t round = 1;
            auto item = [&](int n, auto tag) {
                constexpr bool V = decltype(tag)::value;
                mbar_wait_idle(my_bar + (V ? 8 : 0), round >> 1);
                TRN(192, n);
                if (n + kDqWarps <= last) fetch(n + kDqWarps, Tag<!V>{});
                const uint32_t seen = convert(n, tag);
                asm volatile("cp.async.wait_group 0;" ::: "memory");
                publish(n, seen);
            };
#pragma unroll 1
            for (int n = first + kDqWarps; n <= last; n += kDqWarps, round++) {
                if (n & 1) item(n, Tag<false>{}); else item(n, Tag<true>{});
            }
            asm volatile("barrier.cluster.wait.aligned;" ::: "memory");
        }
    } else {
        const int wg = warp >> 2;
        const int g = lane >> 2, c = lane & 3;
        RowsIn kin;
        rows_load<false>(kin, p, h, wg * 128 + qt * 8 + 2 * (warp & 3) + (lane >> 4), lane & 15);
        asm volatile("barrier.cluster.arrive.relaxed.aligned;" ::: "memory");
        asm volatile("setmaxnreg.inc.sync.aligned.u32 224;");
        {
            const uint8_t* at = rows_store<false>(kin, g_scratch + (size_t)(h * kItems + wg) * kTileBytes + qt * 1024,
                                                  2 * (warp & 3) + (lane >> 4), lane & 15);
            TR(328 + warp);
            const bool never = bar_red_or(4 + wg, 128, (ld_gpu(at) & p.zero[0]) != 0);
            if ((threadIdx.x & 127) == 0) red_gpu(g_flags + (h * kItems + wg) * kFlagStride, never ? 0u : 1u);
            TR(336 + warp);
        }
        const uint32_t rel_addr = mapa(bar_empty, lane & 1);
        const bool rel = lane < 2;
        asm volatile("barrier.cluster.wait.acquire.aligned;" ::: "memory");
        if (rel) mbar_arrive_cluster(rel_addr + 8 * (3 - wg));

        uint32_t q[32];
        {
            mbar_wait(bar_q + 8 * warp, 0);
            TR(344 + warp);
            const uint32_t a = sbase + kSmemVOff + wg * kVSlotBytes + (warp & 3) * 4096 + g * 256 + c * 16;
            uint32_t any = 0;
#pragma unroll
            for (int r = 0; r < 2; r++) {
#pragma unroll
                for (int j = 0; j < 2; j++) {
                    const uint32_t b = a + r * 2048 + ((j * 64) ^ ((g & 1) * 64));
                    const uint4 lo = lds128(b), hi = lds128(b + 128);
                    const uint4 cl = lds128(b + 16384), ch = lds128(b + 16384 + 128);
                    const uint4 sl = lds128(b + 32768), sh = lds128(b + 32768 + 128);
                    uint32_t* ql = q + 8 * j + r;
                    uint32_t* qh = ql + 16;
                    ql[0] = hsub2(hmul2(lo.x, cl.x), hmul2(hi.x, sl.x)); qh[0] = hadd2(hmul2(hi.x, ch.x), hmul2(lo.x, sh.x));
                    ql[2] = hsub2(hmul2(lo.y, cl.y), hmul2(hi.y, sl.y)); qh[2] = hadd2(hmul2(hi.y, ch.y), hmul2(lo.y, sh.y));
                    ql[4] = hsub2(hmul2(lo.z, cl.z), hmul2(hi.z, sl.z)); qh[4] = hadd2(hmul2(hi.z, ch.z), hmul2(lo.z, sh.z));
                    ql[6] = hsub2(hmul2(lo.w, cl.w), hmul2(hi.w, sl.w)); qh[6] = hadd2(hmul2(hi.w, ch.w), hmul2(lo.w, sh.w));
                    any |= (ql[0] & ql[2] & ql[4]) | (ql[6] & qh[0] & qh[2]) | (qh[4] & qh[6]);
                }
            }
            sched_boundary(any & p.zero[3]);
        }

        float s[64], o[kON];
        uint32_t pr[32];
        float ms0, ms1;
        const uint32_t sb4 = (sbase & 0x3FFFF) >> 4;
        const uint64_t dk0 = kDescK | sb4, dv0 = kDescV | (sb4 + (kSmemVOff >> 4));
        const uint32_t id_mine = __shfl_sync(0xffffffffu, 1 + wg, lane), id_other = __shfl_sync(0xffffffffu, 2 - wg, lane);

        {
            float s0[64];
            if (wg == 1) bar_sync(2, 256);
            mbar_wait(bar_full, 0);
            TRC(true, 16 + 48 * wg);
            WG_FENCE();
            gemm_qk(s0, q, dk0);
            WG_COMMIT();
            {
                bar_sync(6 + wg, 128);
                const int t = threadIdx.x & 127;
                asm volatile("st.shared.v4.u32 [%0], {%1,%1,%1,%1};" ::"r"(sbase + kSmemVOff + wg * kVSlotBytes + 32768 + (t >> 3) * 1024 + (t & 7) * 144),
                             "r"(0x3F803F80u) : "memory");
                asm volatile("fence.proxy.async.shared::cta;" ::: "memory");
                __syncwarp();
                if (rel) mbar_arrive_cluster(rel_addr + 8 * (2 + wg));
            }
            wg_wait<0>();
            fence_regs(s0);
            bar_arrive(id_other, 256);
            if (rel) mbar_arrive_cluster(rel_addr);
            sched_boundary(p.zero[4]);
            row_max(s0, ms0, ms1);
            ms0 *= kScale; ms1 *= kScale;
            exp_tile<0, EQK>(s0, ms0, ms1);
            if (wg == 0) exp_tile<EQK, 16>(s0, ms0, ms1);
            mbar_wait(bar_full + 8, 0);
            bar_sync(id_mine, 256);
            TRC(true, 17 + 48 * wg);
            WG_FENCE();
            gemm_qk(s, q, dk0 + (kTileBytes >> 4));
            WG_COMMIT();
            if (wg == 1) exp_tile<EQK, 16>(s0, ms0, ms1);
            pack_tile(pr, s0);
        }
#pragma unroll
        for (int i = 0; i < kON; i++) o[i] = 0.f;

        uint64_t dk = dk0, dv = dv0;
        auto finish = [&](int j, int ks, int vs, uint32_t vpar, uint32_t z) {
            mbar_wait(bar_full + 16 + 8 * vs, vpar);
            fence_regs(o); fence_regs(pr);
            WG_FENCE();
            gemm_pv(o, pr, dv + vs * (kVSlotBytes >> 4));
            WG_COMMIT();
            bar_arrive(id_other, 256);
            wg_wait<1>();
            TRC(TRACE_FULL || j <= 4 || (ks == 1 && wg == 0), 32 + 48 * wg + j);
            fence_regs(s);
            if (rel) mbar_arrive_cluster(rel_addr + 8 * ks);
            exp_tile<0, ESPLIT>(s, ms0, ms1);
            sched_boundary(z);
            wg_wait<0>();
            fence_regs(o); fence_regs(s);
            if (rel) mbar_arrive_cluster(rel_addr + 16 + 8 * vs);
            exp_tile<ESPLIT, 16>(s, ms0, ms1);
            pack_tile(pr, s);
        };
        auto step = [&](int j, int ks, int vs, uint32_t kpar, uint32_t vpar, uint32_t z) {
            mbar_wait(bar_full + 8 * ks, kpar);
            bar_sync(id_mine, 256);
            TRC(TRACE_FULL || j <= 4, 16 + 48 * wg + j);
            fence_regs(s);
            WG_FENCE();
            gemm_qk(s, q, dk + ks * (kTileBytes >> 4));
            WG_COMMIT();
            finish(j, ks, vs, vpar, z);
        };
        finish(1, 1, 0, 0, p.zero[2]);
#pragma unroll 1
        for (int i = 1; i < 8; i++) {
            step(2 * i, 0, 1, i, i + 1, p.zero[0]);
            step(2 * i + 1, 1, 0, i, i, p.zero[1]);
            dk += p.zero[0]; dv += p.zero[0];
        }
        asm volatile("barrier.cluster.arrive.relaxed.aligned;" ::: "memory");

        __nv_bfloat16* op = p.out + (h * kS + qt * 128 + warp * 16 + g) * kD + 8 * c;
        if (wg == 0) bar_sync(1, 256);
        mbar_wait(bar_full + 24, 1);
        fence_regs(o); fence_regs(pr);
        WG_FENCE();
        gemm_pv(o, pr, dv0 + (kVSlotBytes >> 4));
        WG_COMMIT();
        wg_wait<0>();
        TRC(true, 4 + wg);
        fence_regs(o);
        bool ok = store_rows(op, o, rcp(o[64]), rcp(o[66]), p.zero[0]);

        ok = ok && o[64] <= 1.0995116e12f && o[66] <= 1.0995116e12f;
        if (bar_red_or(3, 256, !ok)) {
            float m0 = -INFINITY, m1 = -INFINITY;
#pragma unroll
            for (int i = 0; i < kON; i++) o[i] = 0.f;
            const uint8_t* src = g_scratch + (size_t)h * kItems * kTileBytes;
#pragma unroll 1
            for (int j = 0; j < 16; j++) {
                if (threadIdx.x == 0) {
                    mbar_expect_tx(bar_fb, 2 * kTileBytes);
                    bulk_g2s(sbase, src + (size_t)(j == 0 ? 0 : 2 * j - 1) * kTileBytes, kTileBytes, bar_fb);
                    bulk_g2s(sbase + kSmemVOff, src + (size_t)(2 * j + 2) * kTileBytes, kTileBytes, bar_fb);
                }
                mbar_wait(bar_fb, j & 1);
                fence_regs(s);
                WG_FENCE();
                gemm_qk(s, q, dk0);
                WG_COMMIT();
                wg_wait<0>();
                fence_regs(s);
                float a0, a1;
                row_max(s, a0, a1);
                a0 = fmaxf(a0, m0); a1 = fmaxf(a1, m1);
                const float r0 = a0 == -INFINITY ? 0.f : a0, r1 = a1 == -INFINITY ? 0.f : a1;
                const float al0 = ex2((m0 - r0) * kScale), al1 = ex2((m1 - r1) * kScale);
                m0 = a0; m1 = a1;
                exp_tile<0, 16>(s, r0 * kScale, r1 * kScale);
                pack_tile(pr, s);
#pragma unroll
                for (int n = 0; n < kON / 4; n++) { o[4 * n] *= al0; o[4 * n + 1] *= al0; o[4 * n + 2] *= al1; o[4 * n + 3] *= al1; }
                fence_regs(o); fence_regs(pr);
                WG_FENCE();
                gemm_pv(o, pr, dv0);
                WG_COMMIT();
                wg_wait<0>();
                fence_regs(o);
                bar_sync(3, 256);
            }
            store_rows(op, o, 1.f / o[64], 1.f / o[66], p.zero[0]);
        }
        asm volatile("barrier.cluster.wait.aligned;" ::: "memory");
    }
}

}

extern "C" void kernel_launch(void* const* d_in, const int* in_sizes, int n_in, void* d_out, int out_size) {
    (void)in_sizes; (void)n_in; (void)out_size;
    Params p;
    p.q = (const __nv_bfloat16*)d_in[0];
    p.qk = (const int*)d_in[1];
    p.k_scales = (const __nv_bfloat16*)d_in[2];
    p.k_zeros = (const __nv_bfloat16*)d_in[3];
    p.qv = (const int*)d_in[4];
    p.v_scales = (const __nv_bfloat16*)d_in[5];
    p.v_zeros = (const __nv_bfloat16*)d_in[6];
    p.q_cos = (const __nv_bfloat16*)d_in[7];
    p.q_sin = (const __nv_bfloat16*)d_in[8];
    p.k_cos = (const __nv_bfloat16*)d_in[9];
    p.k_sin = (const __nv_bfloat16*)d_in[10];
    p.out = (__nv_bfloat16*)d_out;
    for (int i = 0; i < 5; i++) p.zero[i] = 0;
    p.t_v0 = 200; p.t_q = 400; p.dt_q = 620; p.t_next = 5900; p.dt_next = 400; p.t_k2 = 2800; p.gap_q = 200; p.k_v1 = 6;
    p.t_poll = 1400; p.stagger = 60; p.lag_q = 110; p.catch_q = 24;
    static int co_resident = -1;
    if (co_resident < 0) {
        cudaFuncSetAttribute(attn_kernel, cudaFuncAttributeMaxDynamicSharedMemorySize, kSmemBytes);
        cudaLaunchConfig_t cfg = {};
        cfg.gridDim = dim3(kH * 16); cfg.blockDim = dim3(384); cfg.dynamicSmemBytes = kSmemBytes;
        cudaLaunchAttribute at;
        at.id = cudaLaunchAttributeClusterDimension;
        at.val.clusterDim.x = 2; at.val.clusterDim.y = 1; at.val.clusterDim.z = 1;
        cfg.attrs = &at; cfg.numAttrs = 1;
        int clusters = 0;
        co_resident = cudaOccupancyMaxActiveClusters(&clusters, attn_kernel, &cfg) == cudaSuccess && clusters >= kH * 8;
        (void)cudaGetLastError();
    }
    if (!co_resident) prefill_kernel<<<kItems * kH * 16, 128>>>(p);
    attn_kernel<<<kH * 16, 384, kSmemBytes>>>(p);
}
```

```cpp
#include <cuda_runtime.h>
#include <cuda_bf16.h>
#include <stdint.h>

namespace {

constexpr int kH = 8, kS = 2048, kD = 128;
constexpr int kItems = 33;
constexpr int kTileBytes = 32768;
constexpr int kVSlotBytes = 49152;
constexpr int kDqWarps = 3;
constexpr int kRawBytes = 12288;
constexpr int kSmemVOff = 2 * kTileBytes;
constexpr int kSmemRawOff = kSmemVOff + 2 * kVSlotBytes;
constexpr int kSmemOutOff = kSmemRawOff + kDqWarps * kRawBytes;
constexpr int kSmemScOff = kSmemOutOff + kDqWarps * 2048;
constexpr int kSmemBarOff = kSmemScOff + kDqWarps * 768;
constexpr int kSmemBytes = kSmemBarOff + 256 + 1024;
constexpr int kFlagStride = 64;
constexpr int kON = 68;
constexpr float kScale = 0.08838834764831845f * 1.4426950408889634f;
constexpr uint32_t kWaitLimit = 1u << 30;
#define ESPLIT 9
#define EQK 8

__device__ __align__(1024) uint8_t g_scratch[(size_t)kH * kItems * kTileBytes];
__device__ __align__(256) unsigned g_flags[kH * kItems * kFlagStride];
__device__ unsigned g_done;

#define TR(idx) do {} while (0)
#define TRG(idx) do {} while (0)
#define TRN(base, n) do {} while (0)
#define TRC(cond, idx) do {} while (0)

struct Params {
    const __nv_bfloat16* q;
    const int* qk;
    const __nv_bfloat16* k_scales;
    const __nv_bfloat16* k_zeros;
    const int* qv;
    const __nv_bfloat16* v_scales;
    const __nv_bfloat16* v_zeros;
    const __nv_bfloat16* q_cos;
    const __nv_bfloat16* q_sin;
    const __nv_bfloat16* k_cos;
    const __nv_bfloat16* k_sin;
    __nv_bfloat16* out;
    uint32_t zero[7];
    int t_v0, t_q, dt_q, t_next, dt_next, t_k2, gap_q, k_v1, t_poll, stagger, lag_q, catch_q;
};

__device__ __forceinline__ uint32_t smem_u32(const void* p) { return (uint32_t)__cvta_generic_to_shared(p); }
__device__ __forceinline__ uint32_t clock32() {
    uint32_t c;
    asm volatile("mov.u32 %0, %%clock;" : "=r"(c));
    return c;
}
__device__ __forceinline__ void wait_until(uint32_t t0, int t) {
    while ((int)(clock32() - t0) < t) {}
    __syncwarp();
}
__device__ __forceinline__ bool elect() {
    uint32_t r;
    asm volatile("{\n.reg .pred p;\nelect.sync _|p, 0xffffffff;\nselp.u32 %0, 1, 0, p;\n}\n" : "=r"(r));
    return r != 0;
}
__device__ __forceinline__ void mbar_init(uint32_t bar, uint32_t count) {
    asm volatile("mbarrier.init.shared::cta.b64 [%0], %1;" ::"r"(bar), "r"(count) : "memory");
}
__device__ __forceinline__ void mbar_expect_tx(uint32_t bar, uint32_t bytes) {
    asm volatile("mbarrier.arrive.expect_tx.shared::cta.b64 _, [%0], %1;" ::"r"(bar), "r"(bytes) : "memory");
}
__device__ __forceinline__ bool mbar_try(uint32_t bar, uint32_t parity) {
    uint32_t ok;
    asm volatile(
        "{\n.reg .pred p;\n"
        "mbarrier.try_wait.parity.shared::cta.b64 p, [%1], %2;\n"
        "selp.u32 %0, 1, 0, p;\n}\n"
        : "=r"(ok)
        : "r"(bar), "r"(parity)
        : "memory");
    return ok != 0;
}
__device__ __forceinline__ void mbar_wait(uint32_t bar, uint32_t parity) {
    if (mbar_try(bar, parity)) return;
    const uint32_t t0 = clock32();
    while (!mbar_try(bar, parity)) {
        if (clock32() - t0 > kWaitLimit) break;
    }
}
__device__ __forceinline__ void mbar_wait_idle(uint32_t bar, uint32_t parity) {
    if (mbar_try(bar, parity)) return;
    const uint32_t t0 = clock32();
    uint32_t ok;
    do {
        asm volatile(
            "{\n.reg .pred p;\n"
            "mbarrier.try_wait.parity.shared::cta.b64 p, [%1], %2, 20000;\n"
            "selp.u32 %0, 1, 0, p;\n}\n"
            : "=r"(ok)
            : "r"(bar), "r"(parity)
            : "memory");
    } while (!ok && clock32() - t0 <= kWaitLimit);
    __syncwarp();
}
__device__ __forceinline__ void mbar_arrive_cluster(uint32_t cluster_addr) {
    asm volatile("mbarrier.arrive.shared::cluster.b64 _, [%0];" ::"r"(cluster_addr) : "memory");
}
__device__ __forceinline__ uint32_t mapa(uint32_t addr, uint32_t rank) {
    uint32_t r;
    asm("mapa.shared::cluster.u32 %0, %1, %2;" : "=r"(r) : "r"(addr), "r"(rank));
    return r;
}
__device__ __forceinline__ void bulk_g2s(uint32_t dst, const void* src, uint32_t bytes, uint32_t bar) {
    asm volatile("cp.async.bulk.shared::cluster.global.mbarrier::complete_tx::bytes [%0], [%1], %2, [%3];" ::"r"(dst),
                 "l"(src), "r"(bytes), "r"(bar)
                 : "memory");
}
__device__ __forceinline__ void bulk_g2s_mc(uint32_t dst, const void* src, uint32_t bytes, uint32_t bar, uint16_t mask) {
    asm volatile(
        "cp.async.bulk.shared::cluster.global.mbarrier::complete_tx::bytes.multicast::cluster [%0], [%1], %2, [%3], %4;" ::"r"(dst),
        "l"(src), "r"(bytes), "r"(bar), "h"(mask)
        : "memory");
}
__device__ __forceinline__ void cp_async_4k(uint32_t dst, const void* src) {
#pragma unroll
    for (int i = 0; i < 8; i++)
        asm volatile("cp.async.cg.shared.global [%0], [%1], 16;" ::"r"(dst + i * 512), "l"((const uint8_t*)src + i * 512) : "memory");
}
__device__ __forceinline__ void bar_sync(int id, int n) { asm volatile("bar.sync %0, %1;" ::"r"(id), "r"(n) : "memory"); }
__device__ __forceinline__ void bar_arrive(int id, int n) { asm volatile("bar.arrive %0, %1;" ::"r"(id), "r"(n) : "memory"); }
__device__ __forceinline__ bool bar_red_or(int id, int n, bool v) {
    uint32_t r;
    asm volatile(
        "{\n.reg .pred p, q;\nsetp.ne.u32 q, %3, 0;\n"
        "bar.red.or.pred p, %1, %2, q;\nselp.u32 %0, 1, 0, p;\n}\n"
        : "=r"(r)
        : "r"(id), "r"(n), "r"((uint32_t)v)
        : "memory");
    return r != 0;
}
__device__ __forceinline__ void sched_boundary(uint32_t zero) {
    asm volatile("{\n.reg .pred p;\nsetp.ne.u32 p, %0, 0;\n@p exit;\n}\n" ::"r"(zero) : "memory");
}
__device__ __forceinline__ float ex2(float x) {
    float y;
    asm("ex2.approx.ftz.f32 %0, %1;" : "=f"(y) : "f"(x));
    return y;
}
__device__ __forceinline__ float rcp(float x) {
    float y;
    asm("rcp.approx.ftz.f32 %0, %1;" : "=f"(y) : "f"(x));
    return y;
}
__device__ __forceinline__ uint32_t pack_bf16(float lo, float hi) {
    uint32_t r;
    asm("cvt.rn.bf16x2.f32 %0, %1, %2;" : "=r"(r) : "f"(hi), "f"(lo));
    return r;
}
__device__ __forceinline__ uint32_t hmul2(uint32_t a, uint32_t b) {
    uint32_t r;
    asm("mul.rn.bf16x2 %0, %1, %2;" : "=r"(r) : "r"(a), "r"(b));
    return r;
}
__device__ __forceinline__ uint32_t hadd2(uint32_t a, uint32_t b) {
    uint32_t r;
    asm("add.rn.bf16x2 %0, %1, %2;" : "=r"(r) : "r"(a), "r"(b));
    return r;
}
__device__ __forceinline__ uint32_t hsub2(uint32_t a, uint32_t b) {
    uint32_t r;
    asm("sub.rn.bf16x2 %0, %1, %2;" : "=r"(r) : "r"(a), "r"(b));
    return r;
}
__device__ __forceinline__ uint32_t hfma2(uint32_t a, uint32_t b, uint32_t c) {
    uint32_t r;
    asm("fma.rn.bf16x2 %0, %1, %2, %3;" : "=r"(r) : "r"(a), "r"(b), "r"(c));
    return r;
}
__device__ __forceinline__ uint4 lds128(uint32_t a) {
    uint4 v;
    asm volatile("ld.shared.v4.u32 {%0,%1,%2,%3}, [%4];" : "=r"(v.x), "=r"(v.y), "=r"(v.z), "=r"(v.w) : "r"(a));
    return v;
}
__device__ __forceinline__ uint2 lds64(uint32_t a) {
    uint2 v;
    asm volatile("ld.shared.v2.u32 {%0,%1}, [%2];" : "=r"(v.x), "=r"(v.y) : "r"(a));
    return v;
}
__device__ __forceinline__ uint32_t lds32(uint32_t a) {
    uint32_t v;
    asm volatile("ld.shared.u32 %0, [%1];" : "=r"(v) : "r"(a));
    return v;
}
__device__ __forceinline__ void sts32(uint32_t a, uint32_t v) { asm volatile("st.shared.u32 [%0], %1;" ::"r"(a), "r"(v) : "memory"); }
__device__ __forceinline__ uint4 ldg128(const void* p) {
    uint4 v;
    asm volatile("ld.global.nc.L1::no_allocate.v4.u32 {%0,%1,%2,%3}, [%4];" : "=r"(v.x), "=r"(v.y), "=r"(v.z), "=r"(v.w) : "l"(p) : "memory");
    return v;
}
__device__ __forceinline__ uint2 ldg64(const void* p) {
    uint2 v;
    asm volatile("ld.global.nc.L1::no_allocate.v2.u32 {%0,%1}, [%2];" : "=r"(v.x), "=r"(v.y) : "l"(p) : "memory");
    return v;
}
__device__ __forceinline__ uint32_t ldg32(const void* p) {
    uint32_t v;
    asm volatile("ld.global.nc.L1::no_allocate.u32 %0, [%1];" : "=r"(v) : "l"(p) : "memory");
    return v;
}
__device__ __forceinline__ uint32_t ld_gpu(const void* p) {
    uint32_t v;
    asm volatile("ld.relaxed.gpu.global.u32 %0, [%1];" : "=r"(v) : "l"(p) : "memory");
    return v;
}
__device__ __forceinline__ void red_gpu(unsigned* p, uint32_t v) {
    asm volatile("red.relaxed.gpu.global.add.u32 [%0], %1;" ::"l"(p), "r"(v) : "memory");
}

#define WG_FENCE() asm volatile("wgmma.fence.sync.aligned;" ::: "memory")
#define WG_COMMIT() asm volatile("wgmma.commit_group.sync.aligned;" ::: "memory")
template <int N>
__device__ __forceinline__ void wg_wait() {
    asm volatile("wgmma.wait_group.sync.aligned %0;" ::"n"(N) : "memory");
}
template <int ACC>
__device__ __forceinline__ void wgmma_qk(float (&d)[64], uint32_t a0, uint32_t a1, uint32_t a2, uint32_t a3, uint64_t db) {
    asm volatile(
        "{\n.reg .pred p;\nsetp.ne.b32 p, %69, 0;\n"
        "wgmma.mma_async.sync.aligned.m64n128k16.f32.bf16.bf16 "
        "{%0,%1,%2,%3,%4,%5,%6,%7,%8,%9,%10,%11,%12,%13,%14,%15,%16,%17,%18,%19,%20,%21,%22,%23,"
        "%24,%25,%26,%27,%28,%29,%30,%31,%32,%33,%34,%35,%36,%37,%38,%39,%40,%41,%42,%43,%44,%45,%46,%47,"
        "%48,%49,%50,%51,%52,%53,%54,%55,%56,%57,%58,%59,%60,%61,%62,%63}, {%64,%65,%66,%67}, %68, p, 1, 1, 0;\n}\n"
        : "+f"(d[0]), "+f"(d[1]), "+f"(d[2]), "+f"(d[3]), "+f"(d[4]), "+f"(d[5]), "+f"(d[6]), "+f"(d[7]),
          "+f"(d[8]), "+f"(d[9]), "+f"(d[10]), "+f"(d[11]), "+f"(d[12]), "+f"(d[13]), "+f"(d[14]), "+f"(d[15]),
          "+f"(d[16]), "+f"(d[17]), "+f"(d[18]), "+f"(d[19]), "+f"(d[20]), "+f"(d[21]), "+f"(d[22]), "+f"(d[23]),
          "+f"(d[24]), "+f"(d[25]), "+f"(d[26]), "+f"(d[27]), "+f"(d[28]), "+f"(d[29]), "+f"(d[30]), "+f"(d[31]),
          "+f"(d[32]), "+f"(d[33]), "+f"(d[34]), "+f"(d[35]), "+f"(d[36]), "+f"(d[37]), "+f"(d[38]), "+f"(d[39]),
          "+f"(d[40]), "+f"(d[41]), "+f"(d[42]), "+f"(d[43]), "+f"(d[44]), "+f"(d[45]), "+f"(d[46]), "+f"(d[47]),
          "+f"(d[48]), "+f"(d[49]), "+f"(d[50]), "+f"(d[51]), "+f"(d[52]), "+f"(d[53]), "+f"(d[54]), "+f"(d[55]),
          "+f"(d[56]), "+f"(d[57]), "+f"(d[58]), "+f"(d[59]), "+f"(d[60]), "+f"(d[61]), "+f"(d[62]), "+f"(d[63])
        : "r"(a0), "r"(a1), "r"(a2), "r"(a3), "l"(db), "n"(ACC));
}
__device__ __forceinline__ void wgmma_pv(float (&d)[kON], uint32_t a0, uint32_t a1, uint32_t a2, uint32_t a3, uint64_t db) {
    asm volatile(
        "wgmma.mma_async.sync.aligned.m64n136k16.f32.bf16.bf16 "
        "{%0,%1,%2,%3,%4,%5,%6,%7,%8,%9,%10,%11,%12,%13,%14,%15,%16,%17,%18,%19,%20,%21,%22,%23,"
        "%24,%25,%26,%27,%28,%29,%30,%31,%32,%33,%34,%35,%36,%37,%38,%39,%40,%41,%42,%43,%44,%45,%46,%47,"
        "%48,%49,%50,%51,%52,%53,%54,%55,%56,%57,%58,%59,%60,%61,%62,%63,%64,%65,%66,%67}, {%68,%69,%70,%71}, %72, 1, 1, 1, 1;\n"
        : "+f"(d[0]), "+f"(d[1]), "+f"(d[2]), "+f"(d[3]), "+f"(d[4]), "+f"(d[5]), "+f"(d[6]), "+f"(d[7]),
          "+f"(d[8]), "+f"(d[9]), "+f"(d[10]), "+f"(d[11]), "+f"(d[12]), "+f"(d[13]), "+f"(d[14]), "+f"(d[15]),
          "+f"(d[16]), "+f"(d[17]), "+f"(d[18]), "+f"(d[19]), "+f"(d[20]), "+f"(d[21]), "+f"(d[22]), "+f"(d[23]),
          "+f"(d[24]), "+f"(d[25]), "+f"(d[26]), "+f"(d[27]), "+f"(d[28]), "+f"(d[29]), "+f"(d[30]), "+f"(d[31]),
          "+f"(d[32]), "+f"(d[33]), "+f"(d[34]), "+f"(d[35]), "+f"(d[36]), "+f"(d[37]), "+f"(d[38]), "+f"(d[39]),
          "+f"(d[40]), "+f"(d[41]), "+f"(d[42]), "+f"(d[43]), "+f"(d[44]), "+f"(d[45]), "+f"(d[46]), "+f"(d[47]),
          "+f"(d[48]), "+f"(d[49]), "+f"(d[50]), "+f"(d[51]), "+f"(d[52]), "+f"(d[53]), "+f"(d[54]), "+f"(d[55]),
          "+f"(d[56]), "+f"(d[57]), "+f"(d[58]), "+f"(d[59]), "+f"(d[60]), "+f"(d[61]), "+f"(d[62]), "+f"(d[63]),
          "+f"(d[64]), "+f"(d[65]), "+f"(d[66]), "+f"(d[67])
        : "r"(a0), "r"(a1), "r"(a2), "r"(a3), "l"(db));
}
__device__ __forceinline__ void wgmma_pv_hi(float (&d)[36], uint32_t a0, uint32_t a1, uint32_t a2, uint32_t a3, uint64_t db) {
    asm volatile(
        "wgmma.mma_async.sync.aligned.m64n72k16.f32.bf16.bf16 "
        "{%0,%1,%2,%3,%4,%5,%6,%7,%8,%9,%10,%11,%12,%13,%14,%15,%16,%17,%18,%19,%20,%21,%22,%23,"
        "%24,%25,%26,%27,%28,%29,%30,%31,%32,%33,%34,%35}, {%36,%37,%38,%39}, %40, 1, 1, 1, 1;\n"
        : "+f"(d[0]), "+f"(d[1]), "+f"(d[2]), "+f"(d[3]), "+f"(d[4]), "+f"(d[5]), "+f"(d[6]), "+f"(d[7]),
          "+f"(d[8]), "+f"(d[9]), "+f"(d[10]), "+f"(d[11]), "+f"(d[12]), "+f"(d[13]), "+f"(d[14]), "+f"(d[15]),
          "+f"(d[16]), "+f"(d[17]), "+f"(d[18]), "+f"(d[19]), "+f"(d[20]), "+f"(d[21]), "+f"(d[22]), "+f"(d[23]),
          "+f"(d[24]), "+f"(d[25]), "+f"(d[26]), "+f"(d[27]), "+f"(d[28]), "+f"(d[29]), "+f"(d[30]), "+f"(d[31]),
          "+f"(d[32]), "+f"(d[33]), "+f"(d[34]), "+f"(d[35])
        : "r"(a0), "r"(a1), "r"(a2), "r"(a3), "l"(db));
}
__device__ __forceinline__ void wgmma_pv_lo(float (&d)[32], uint32_t a0, uint32_t a1, uint32_t a2, uint32_t a3, uint64_t db) {
    asm volatile(
        "wgmma.mma_async.sync.aligned.m64n64k16.f32.bf16.bf16 "
        "{%0,%1,%2,%3,%4,%5,%6,%7,%8,%9,%10,%11,%12,%13,%14,%15,%16,%17,%18,%19,%20,%21,%22,%23,"
        "%24,%25,%26,%27,%28,%29,%30,%31}, {%32,%33,%34,%35}, %36, 1, 1, 1, 1;\n"
        : "+f"(d[0]), "+f"(d[1]), "+f"(d[2]), "+f"(d[3]), "+f"(d[4]), "+f"(d[5]), "+f"(d[6]), "+f"(d[7]),
          "+f"(d[8]), "+f"(d[9]), "+f"(d[10]), "+f"(d[11]), "+f"(d[12]), "+f"(d[13]), "+f"(d[14]), "+f"(d[15]),
          "+f"(d[16]), "+f"(d[17]), "+f"(d[18]), "+f"(d[19]), "+f"(d[20]), "+f"(d[21]), "+f"(d[22]), "+f"(d[23]),
          "+f"(d[24]), "+f"(d[25]), "+f"(d[26]), "+f"(d[27]), "+f"(d[28]), "+f"(d[29]), "+f"(d[30]), "+f"(d[31])
        : "r"(a0), "r"(a1), "r"(a2), "r"(a3), "l"(db));
}
template <int N>
__device__ __forceinline__ void fence_regs(float (&d)[N]) {
#pragma unroll
    for (int i = 0; i < N; i++) asm volatile("" : "+f"(d[i])::"memory");
}
__device__ __forceinline__ void fence_regs(uint32_t (&d)[32]) {
#pragma unroll
    for (int i = 0; i < 32; i++) asm volatile("" : "+r"(d[i])::"memory");
}
constexpr uint64_t kDescK = (uint64_t(1) << 62) | (uint64_t(1024 >> 4) << 32) | (uint64_t(1) << 16);
constexpr uint64_t kDescV = (uint64_t(1) << 62) | (uint64_t(1024 >> 4) << 32) | (uint64_t(16384 >> 4) << 16);

__device__ __forceinline__ void gemm_qk(float (&s)[64], const uint32_t (&q)[32], uint64_t d) {
    wgmma_qk<0>(s, q[0], q[1], q[2], q[3], d);
#pragma unroll
    for (int kk = 1; kk < 8; kk++)
        wgmma_qk<1>(s, q[4 * kk], q[4 * kk + 1], q[4 * kk + 2], q[4 * kk + 3], d + (((kk >> 2) * 16384 + (kk & 3) * 32) >> 4));
}
__device__ __forceinline__ void gemm_pv(float (&o)[kON], const uint32_t (&p)[32], uint64_t d) {
#pragma unroll
    for (int kk = 0; kk < 8; kk++) wgmma_pv(o, p[4 * kk], p[4 * kk + 1], p[4 * kk + 2], p[4 * kk + 3], d + ((kk * 2048) >> 4));
}

__device__ __forceinline__ void dequant4(uint32_t (&v)[4], uint32_t sc, uint32_t zp) {
    const uint32_t s0 = __byte_perm(sc, 0, 0x1010), s1 = __byte_perm(sc, 0, 0x3232);
    const uint32_t z0 = __byte_perm(zp, 0, 0x1010), z1 = __byte_perm(zp, 0, 0x3232);
    v[0] = hmul2(hsub2(v[0], z0), s0); v[1] = hmul2(hsub2(v[1], z0), s0);
    v[2] = hmul2(hsub2(v[2], z1), s1); v[3] = hmul2(hsub2(v[3], z1), s1);
}
__device__ __forceinline__ void to_bf16(uint32_t (&v)[4], const uint4& lo, const uint4& hi) {
    v[0] = pack_bf16((float)(int)lo.x, (float)(int)lo.y); v[1] = pack_bf16((float)(int)lo.z, (float)(int)lo.w);
    v[2] = pack_bf16((float)(int)hi.x, (float)(int)hi.y); v[3] = pack_bf16((float)(int)hi.z, (float)(int)hi.w);
}
__device__ __forceinline__ void rope4(uint32_t (&v)[4], const uint2& cl, const uint2& ch, const uint2& sl, const uint2& sh) {
    const uint32_t r0 = hsub2(hmul2(v[0], cl.x), hmul2(v[2], sl.x)), r1 = hsub2(hmul2(v[1], cl.y), hmul2(v[3], sl.y));
    const uint32_t r2 = hadd2(hmul2(v[2], ch.x), hmul2(v[0], sh.x)), r3 = hadd2(hmul2(v[3], ch.y), hmul2(v[1], sh.y));
    v[0] = r0; v[1] = r1; v[2] = r2; v[3] = r3;
}

template <bool IS_V>
__device__ __forceinline__ void dequant_slice(uint32_t ia, uint32_t ca, uint32_t oa, uint32_t sc, uint32_t zp) {
    uint4 lo = lds128(ia), hi = lds128(ia + 256);
#pragma unroll
    for (int it = 0; it < 4; it++) {
        uint2 cl, ch, sl, sh;
        if (!IS_V) {
            const uint32_t a = ca ^ ((it >> 1) * 64 + (it & 1) * 8);
            cl = lds64(a); sl = lds64(a + 2048); ch = lds64(a + 128); sh = lds64(a + 2048 + 128);
        }
        uint32_t v[4];
        to_bf16(v, lo, hi);
        if (it < 3) {
            const uint32_t a = ia ^ (((it + 1) >> 1) * 128 + ((it + 1) & 1) * 16);
            lo = lds128(a); hi = lds128(a + 256);
        }
        dequant4(v, sc, zp);
        if (!IS_V) rope4(v, cl, ch, sl, sh);
        const uint32_t o0 = oa ^ (it << 5), o1 = oa ^ ((it << 5) | 16);
        sts32(o0, v[0]); sts32(o1, v[1]); sts32(o0 + 1024, v[2]); sts32(o1 + 1024, v[3]);
    }
}

struct RowsIn { uint4 lo, hi; uint2 cl, ch, sl, sh; uint32_t sc, zp; };
template <bool IS_V>
__device__ __forceinline__ void rows_load(RowsIn& x, const Params& p, int h, int row, int mp) {
    const int hr = h * kS + row;
    const int* ints = (IS_V ? p.qv : p.qk) + hr * kD + 4 * mp;
    x.lo = ldg128(ints); x.hi = ldg128(ints + 64);
    if (!IS_V) {
        x.cl = ldg64(p.k_cos + row * kD + 4 * mp); x.ch = ldg64(p.k_cos + row * kD + 64 + 4 * mp);
        x.sl = ldg64(p.k_sin + row * kD + 4 * mp); x.sh = ldg64(p.k_sin + row * kD + 64 + 4 * mp);
    }
    x.sc = ldg32((IS_V ? p.v_scales : p.k_scales) + hr * 2); x.zp = ldg32((IS_V ? p.v_zeros : p.k_zeros) + hr * 2);
}
template <bool IS_V>
__device__ __forceinline__ uint8_t* rows_store(const RowsIn& a, uint8_t* slice, int r, int mp) {
    const int j = mp >> 3, c = (mp >> 1) & 3, b = mp & 1;
    uint32_t v[4];
    to_bf16(v, a.lo, a.hi);
    dequant4(v, a.sc, a.zp);
    if (!IS_V) rope4(v, a.cl, a.ch, a.sl, a.sh);
    const bool c0 = c & 1, c1 = c & 2;
    uint32_t x = __shfl_xor_sync(0xffffffffu, c0 ? v[0] : v[1], 2), y = __shfl_xor_sync(0xffffffffu, c0 ? v[2] : v[3], 2);
    const uint32_t a0 = c0 ? x : v[0], a1 = c0 ? v[1] : x, a2 = c0 ? y : v[2], a3 = c0 ? v[3] : y;
    x = __shfl_xor_sync(0xffffffffu, c1 ? a0 : a2, 4); y = __shfl_xor_sync(0xffffffffu, c1 ? a1 : a3, 4);
    uint8_t* dst = slice + (c >> 1) * 16384 + r * 128 + (((4 * j + 2 * b + (c & 1)) ^ r) << 4);
    *reinterpret_cast<uint4*>(dst) = make_uint4(c1 ? x : a0, c1 ? y : a1, c1 ? a2 : x, c1 ? a3 : y);
    return dst;
}

__global__ void __launch_bounds__(128) prefill_kernel(const __grid_constant__ Params p) {
    const int slice = blockIdx.x & 15, h = (blockIdx.x >> 4) & 7, n = blockIdx.x >> 7;
    if (n == kItems - 2) return;
    const int r = threadIdx.x >> 4, mp = threadIdx.x & 15;
    const bool is_v = n != 0 && !(n & 1);
    const int row = (is_v ? (n >> 1) - 1 : (n + 1) >> 1) * 128 + slice * 8 + r;
    uint8_t* dst = g_scratch + (size_t)(h * kItems + n) * kTileBytes + slice * 1024;
    RowsIn x;
    if (is_v) { rows_load<true>(x, p, h, row, mp); rows_store<true>(x, dst, r, mp); }
    else { rows_load<false>(x, p, h, row, mp); rows_store<false>(x, dst, r, mp); }
    if (threadIdx.x == 0 && slice == 0) g_flags[(h * kItems + n) * kFlagStride] = 16;
}

template <int N0, int N1>
__device__ __forceinline__ void exp_tile(float (&s)[64], float ms0, float ms1) {
    if (N0 == 0) {
#pragma unroll
        for (int i = 0; i < 64; i++) s[i] = fmaf(s[i], kScale, (i & 2) ? -ms1 : -ms0);
    }
#pragma unroll
    for (int i = 4 * N0; i < 4 * N1; i++) s[i] = ex2(s[i]);
}
__device__ __forceinline__ void row_max(const float (&s)[64], float& m0, float& m1) {
    float a0 = fmaxf(s[0], s[1]), a1 = fmaxf(s[2], s[3]), b0 = fmaxf(s[4], s[5]), b1 = fmaxf(s[6], s[7]);
#pragma unroll
    for (int n = 2; n < 16; n += 2) {
        a0 = fmaxf(a0, fmaxf(s[4 * n], s[4 * n + 1])); a1 = fmaxf(a1, fmaxf(s[4 * n + 2], s[4 * n + 3]));
        b0 = fmaxf(b0, fmaxf(s[4 * n + 4], s[4 * n + 5])); b1 = fmaxf(b1, fmaxf(s[4 * n + 6], s[4 * n + 7]));
    }
    m0 = fmaxf(a0, b0); m1 = fmaxf(a1, b1);
    m0 = fmaxf(m0, __shfl_xor_sync(0xffffffffu, m0, 1)); m1 = fmaxf(m1, __shfl_xor_sync(0xffffffffu, m1, 1));
    m0 = fmaxf(m0, __shfl_xor_sync(0xffffffffu, m0, 2)); m1 = fmaxf(m1, __shfl_xor_sync(0xffffffffu, m1, 2));
}
__device__ __forceinline__ void pack_tile(uint32_t (&pr)[32], const float (&s)[64]) {
#pragma unroll
    for (int i = 0; i < 32; i++) pr[i] = pack_bf16(s[2 * i], s[2 * i + 1]);
}
template <int N>
__device__ __forceinline__ void store_half(__nv_bfloat16* op, uint4 (&v)[4], const float (&o)[N], int b, float i0, float i1) {
#pragma unroll
    for (int j = 0; j < 2; j++) {
        uint4 &v0 = v[2 * j], &v1 = v[2 * j + 1];
        const float* x = o + b + 16 * j;
        v0.x = pack_bf16(x[0] * i0, x[1] * i0);  v0.y = pack_bf16(x[4] * i0, x[5] * i0);
        v0.z = pack_bf16(x[8] * i0, x[9] * i0);  v0.w = pack_bf16(x[12] * i0, x[13] * i0);
        *reinterpret_cast<uint4*>(op + 32 * j) = v0;
        v1.x = pack_bf16(x[2] * i1, x[3] * i1);  v1.y = pack_bf16(x[6] * i1, x[7] * i1);
        v1.z = pack_bf16(x[10] * i1, x[11] * i1); v1.w = pack_bf16(x[14] * i1, x[15] * i1);
        *reinterpret_cast<uint4*>(op + 8 * kD + 32 * j) = v1;
    }
}
__device__ __forceinline__ bool all_finite(const uint4 (&u)[4], const uint4 (&v)[4], uint32_t zero) {
    uint32_t a[4] = {0, 0, 0, 0};
#pragma unroll
    for (int j = 0; j < 4; j++) {
        a[0] = hfma2(u[j].x, zero, hfma2(v[j].x, zero, a[0])); a[1] = hfma2(u[j].y, zero, hfma2(v[j].y, zero, a[1]));
        a[2] = hfma2(u[j].z, zero, hfma2(v[j].z, zero, a[2])); a[3] = hfma2(u[j].w, zero, hfma2(v[j].w, zero, a[3]));
    }
    return ((a[0] | a[1] | a[2] | a[3]) & 0x7fff7fffu) == 0;
}

template <bool B> struct Tag { static constexpr bool value = B; };

__global__ void __cluster_dims__(2, 1, 1) __launch_bounds__(384, 1) attn_kernel(const __grid_constant__ Params p) {
    extern __shared__ uint8_t smem_raw[];
    const uint32_t sbase = (smem_u32(smem_raw) + 1023) & ~1023u;
    const uint32_t bar_full = sbase + kSmemBarOff;
    const uint32_t bar_empty = bar_full + 32;
    const uint32_t bar_raw = bar_empty + 32;
    const uint32_t bar_q = bar_raw + 16 * kDqWarps;
    const uint32_t bar_fb = bar_q + 64;

    const int warp = __shfl_sync(0xffffffffu, threadIdx.x >> 5, 0), lane = threadIdx.x & 31;
    const int h = blockIdx.x >> 4, qt = blockIdx.x & 15;

    if (warp >= 8) {
        asm volatile("setmaxnreg.dec.sync.aligned.u32 56;");
        if (warp == 8) {
            const uint32_t t0 = clock32();
            TR(0); TRG(1);
            const unsigned* fp = g_flags + (h * kItems + lane) * kFlagStride;
            uint32_t early = 0;
            if (lane < 8) early = ld_gpu(fp);
            if (elect()) {
                for (int i = 0; i < 4; i++) {
                    mbar_init(bar_full + 8 * i, 1);
                    mbar_init(bar_empty + 8 * i, 16);
                }
                mbar_init(bar_fb, 1);
                asm volatile("fence.mbarrier_init.release.cluster;" ::: "memory");
            }
            __syncwarp();
            asm volatile("barrier.cluster.arrive.relaxed.aligned;" ::: "memory");
            asm volatile("barrier.cluster.wait.acquire.aligned;" ::: "memory");
            const uint32_t rank = blockIdx.x & 1;
            const uint8_t* src = g_scratch + (size_t)h * kItems * kTileBytes + rank * (kTileBytes / 2);
            uint32_t ready = __ballot_sync(0xffffffffu, early >= 16), parity = 3;
            wait_until(t0, p.t_poll);
#pragma unroll 1
            for (int n = 0; n < kItems; n++, ready >>= 1, src += kTileBytes, fp += kFlagStride) {
                if (n == kItems - 2) continue;
                const bool mine = lane < 8 && n + lane < kItems;
                if (!(ready & 1)) {
                    const uint32_t t1 = clock32();
                    do {
                        ready = __ballot_sync(0xffffffffu, mine && ld_gpu(fp) >= 16);
                    } while (!(ready & 1) && !__any_sync(0xffffffffu, clock32() - t1 > kWaitLimit));
                    asm volatile("fence.acquire.gpu;" ::: "memory");
                }
                TRN(128, n);
                const bool is_v = n != 0 && !(n & 1);
                const int odd = (((n + 1) >> 1) & 1) ^ (is_v ? 1 : 0);
                const int slot = (is_v ? 2 : 0) + odd;
                const bool peek = !(ready & 2);
                uint32_t ahead = 0;
                if (peek && mine) ahead = ld_gpu(fp);
                mbar_wait_idle(bar_empty + 8 * slot, (parity >> slot) & 1);
                TRN(160, n);
                if (elect()) {
                    mbar_expect_tx(bar_full + 8 * slot, kTileBytes);
                    const uint32_t dst = sbase + (is_v ? kSmemVOff + odd * kVSlotBytes : odd * kTileBytes);
                    bulk_g2s_mc(dst + rank * (kTileBytes / 2), src, kTileBytes / 2, bar_full + 8 * slot, (uint16_t)3);
                }
                parity ^= 1u << slot;
                if (peek) {
                    ready = __ballot_sync(0xffffffffu, ahead >= 16);
                    asm volatile("fence.acquire.gpu;" ::: "memory");
                }
            }
            uint32_t ticket = 0;
            if (lane == 0) ticket = atomicAdd(&g_done, 1u);
            if (__shfl_sync(0xffffffffu, ticket, 0) == gridDim.x - 1) {
                for (int i = lane; i < kH * kItems; i += 32) g_flags[i * kFlagStride] = 0;
                if (lane == 0) g_done = 0;
            }
        } else {
            const int w = warp - 9;
            const uint32_t t0 = clock32() + p.stagger * h;
            const int first = w == 0 ? 2 : 5 - w;
            const int last = first == 4 ? 28 : kItems - 1;
            const uint32_t my_bar = bar_raw + 16 * w;
            const uint32_t my_raw = sbase + kSmemRawOff + w * kRawBytes;
            const uint32_t my_out = sbase + kSmemOutOff + w * 2048;
            const uint32_t my_sc = sbase + kSmemScOff + w * 768;
            auto fetch = [&](int n, auto tag) {
                constexpr bool V = decltype(tag)::value;
                const int row0 = (V ? (n >> 1) - 1 : (n + 1) >> 1) * 128 + qt * 8;
                if (elect()) {
                    if (V) {
                        mbar_expect_tx(my_bar + 8, 4096);
                        bulk_g2s(my_raw + 8192, p.qv + (h * kS + row0) * kD, 4096, my_bar + 8);
                    } else {
                        mbar_expect_tx(my_bar, 8192);
                        bulk_g2s(my_raw, p.qk + (h * kS + row0) * kD, 4096, my_bar);
                        bulk_g2s(my_raw + 4096, p.k_cos + row0 * kD, 2048, my_bar);
                        bulk_g2s(my_raw + 6144, p.k_sin + row0 * kD, 2048, my_bar);
                    }
                }
            };
            auto fetch_scales = [&](int k) {
                const int n = first + 3 * k;
                const int hr = h * kS + ((n & 1) ? (n + 1) >> 1 : (n >> 1) - 1) * 128 + qt * 8 + (lane & 7);
                const __nv_bfloat16* base = (n & 1) ? ((lane & 8) ? p.k_zeros : p.k_scales) : ((lane & 8) ? p.v_zeros : p.v_scales);
                if (n <= last) asm volatile("cp.async.ca.shared.global [%0], [%1], 4;" ::"r"(my_sc + k * 64 + (lane & 15) * 4), "l"(base + hr * 2) : "memory");
            };
            if (elect()) {
                mbar_init(my_bar, 1); mbar_init(my_bar + 8, 1);
                if (w == 1) for (int i = 0; i < 8; i++) mbar_init(bar_q + 8 * i, 33);
                asm volatile("fence.mbarrier_init.release.cluster;" ::: "memory");
            }
            __syncwarp();
            asm volatile("barrier.cluster.arrive.relaxed.aligned;" ::: "memory");
            fetch_scales(lane >> 4);
            asm volatile("cp.async.commit_group;" ::: "memory");
            if (w == 1) {
#pragma unroll 1
                for (int k = 0; k < 8; k++) {
                    const int row = qt * 128 + k * 16;
                    const uint32_t d = sbase + kSmemVOff + (k >> 2) * kVSlotBytes + (k & 3) * 4096, bar = bar_q + 8 * k;
                    wait_until(t0, p.t_q + h * p.lag_q + k * (p.dt_q - h * p.catch_q) + (k >> 2) * p.gap_q);
                    cp_async_4k(d + ((lane * 16) ^ ((lane & 16) << 2)), p.q + (h * kS + row) * kD + lane * 8);
                    asm volatile("cp.async.mbarrier.arrive.noinc.shared::cta.b64 [%0];" ::"r"(bar) : "memory");
                    if (elect()) {
                        mbar_expect_tx(bar, 8192);
                        bulk_g2s(d + 16384, p.q_cos + row * kD, 4096, bar);
                        bulk_g2s(d + 32768, p.q_sin + row * kD, 4096, bar);
                    }
                    if (k == p.k_v1) fetch(4, Tag<true>{});
                }
                TR(10);
            } else {
                wait_until(t0, w == 0 ? p.t_v0 : p.t_k2);
                if (w == 0) fetch(2, Tag<true>{}); else fetch(3, Tag<false>{});
            }
            const int r = lane >> 2, c = lane & 3, x = r & 3;
            const uint32_t ia = my_raw + r * 512 + c * 32 + (x >> 1) * 128 + (x & 1) * 16;
            const uint32_t ca = my_raw + 4096 + r * 256 + c * 16 + (x >> 1) * 64 + (x & 1) * 8;
            const uint32_t oa = my_out + r * 128 + c * 4 + (((2 * x) ^ r) << 4);
            const int back = (lane & 16) * 1024 + (lane & 15) * 64 - lane * 16;
            uint8_t* dst = g_scratch + (size_t)(h * kItems + first) * kTileBytes + qt * 1024 + lane * 16;
            uint32_t sa = my_sc + r * 4;
            auto convert = [&](int n, auto tag) {
                constexpr bool V = decltype(tag)::value;
                dequant_slice<V>(ia + (V ? 8192 : 0), ca, oa, lds32(sa), lds32(sa + 32));
                __syncwarp();
                const uint4 v0 = lds128(my_out + lane * 16), v1 = lds128(my_out + 512 + lane * 16);
                const uint4 v2 = lds128(my_out + 1024 + lane * 16), v3 = lds128(my_out + 1536 + lane * 16);
                uint4* d = reinterpret_cast<uint4*>(dst);
                d[0] = v0; d[32] = v1; d[1024] = v2; d[1056] = v3;
                TRN(256, n);
                return ld_gpu(dst + back);
            };
            auto publish = [&](int n, uint32_t seen) {
                const uint32_t one = 1u + (__reduce_or_sync(0xffffffffu, seen) & p.zero[0]);
                if (elect()) red_gpu(g_flags + (h * kItems + n) * kFlagStride, one);
                TRN(224, n);
                dst += (size_t)kDqWarps * kTileBytes;
                sa += 64;
            };
            auto round0 = [&](auto tag) {
                constexpr bool V = decltype(tag)::value;
                asm volatile("cp.async.wait_group 0;" ::: "memory");
                mbar_wait_idle(my_bar + (V ? 8 : 0), 0);
                __syncwarp();
                TRN(192, first);
                const uint32_t seen = convert(first, tag);
                const int due = p.t_next + (first - 2) * p.dt_next;
                const bool soon = __any_sync(0xffffffffu, (int)(clock32() - t0) + 800 >= due);
                if (!soon) publish(first, seen);
                wait_until(t0, due);
                fetch(first + kDqWarps, Tag<!V>{});
                if (soon) publish(first, seen);
            };
            if (first & 1) round0(Tag<false>{}); else round0(Tag<true>{});
#pragma unroll 1
            for (int k = 2; k < 12; k += 2) fetch_scales(k + (lane >> 4));
            asm volatile("cp.async.commit_group;" ::: "memory");
            uint32_t round = 1;
            auto item = [&](int n, auto tag) {
                constexpr bool V = decltype(tag)::value;
                mbar_wait_idle(my_bar + (V ? 8 : 0), round >> 1);
                TRN(192, n);
                if (n + kDqWarps <= last) fetch(n + kDqWarps, Tag<!V>{});
                const uint32_t seen = convert(n, tag);
                asm volatile("cp.async.wait_group 0;" ::: "memory");
                publish(n, seen);
            };
#pragma unroll 1
            for (int n = first + kDqWarps; n <= last; n += kDqWarps, round++) {
                if (n & 1) item(n, Tag<false>{}); else item(n, Tag<true>{});
            }
            asm volatile("barrier.cluster.wait.aligned;" ::: "memory");
        }
    } else {
        const int wg = warp >> 2;
        const int g = lane >> 2, c = lane & 3;
        RowsIn kin;
        rows_load<false>(kin, p, h, wg * 128 + qt * 8 + 2 * (warp & 3) + (lane >> 4), lane & 15);
        asm volatile("barrier.cluster.arrive.relaxed.aligned;" ::: "memory");
        asm volatile("setmaxnreg.inc.sync.aligned.u32 224;");
        {
            const uint8_t* at = rows_store<false>(kin, g_scratch + (size_t)(h * kItems + wg) * kTileBytes + qt * 1024,
                                                  2 * (warp & 3) + (lane >> 4), lane & 15);
            TR(328 + warp);
            const bool never = bar_red_or(4 + wg, 128, (ld_gpu(at) & p.zero[0]) != 0);
            if ((threadIdx.x & 127) == 0) red_gpu(g_flags + (h * kItems + wg) * kFlagStride, never ? 0u : 1u);
            TR(336 + warp);
        }
        const uint32_t rel_addr = mapa(bar_empty, lane & 1);
        const bool rel = lane < 2;
        asm volatile("barrier.cluster.wait.acquire.aligned;" ::: "memory");
        if (rel) mbar_arrive_cluster(rel_addr + 8 * (3 - wg));

        uint32_t q[32];
        {
            mbar_wait(bar_q + 8 * warp, 0);
            TR(344 + warp);
            const uint32_t a = sbase + kSmemVOff + wg * kVSlotBytes + (warp & 3) * 4096 + g * 256 + c * 16;
            uint32_t any = 0;
#pragma unroll
            for (int r = 0; r < 2; r++) {
#pragma unroll
                for (int j = 0; j < 2; j++) {
                    const uint32_t bq = a + r * 2048 + ((j * 64) ^ ((g & 1) * 64)), bt = a + r * 2048 + j * 64;
                    const uint4 lo = lds128(bq), hi = lds128(bq + 128);
                    const uint4 cl = lds128(bt + 16384), ch = lds128(bt + 16384 + 128);
                    const uint4 sl = lds128(bt + 32768), sh = lds128(bt + 32768 + 128);
                    uint32_t* ql = q + 8 * j + r;
                    uint32_t* qh = ql + 16;
                    ql[0] = hsub2(hmul2(lo.x, cl.x), hmul2(hi.x, sl.x)); qh[0] = hadd2(hmul2(hi.x, ch.x), hmul2(lo.x, sh.x));
                    ql[2] = hsub2(hmul2(lo.y, cl.y), hmul2(hi.y, sl.y)); qh[2] = hadd2(hmul2(hi.y, ch.y), hmul2(lo.y, sh.y));
                    ql[4] = hsub2(hmul2(lo.z, cl.z), hmul2(hi.z, sl.z)); qh[4] = hadd2(hmul2(hi.z, ch.z), hmul2(lo.z, sh.z));
                    ql[6] = hsub2(hmul2(lo.w, cl.w), hmul2(hi.w, sl.w)); qh[6] = hadd2(hmul2(hi.w, ch.w), hmul2(lo.w, sh.w));
                    any |= (ql[0] & ql[2] & ql[4]) | (ql[6] & qh[0] & qh[2]) | (qh[4] & qh[6]);
                }
            }
            sched_boundary(any & p.zero[3]);
        }

        float s[64], o[kON];
        uint32_t pr[32];
        float ms0, ms1;
        const uint32_t sb4 = (sbase & 0x3FFFF) >> 4;
        const uint64_t dk0 = kDescK | sb4, dv0 = kDescV | (sb4 + (kSmemVOff >> 4));
        const uint32_t id_mine = __shfl_sync(0xffffffffu, 1 + wg, lane), id_other = __shfl_sync(0xffffffffu, 2 - wg, lane);

        {
            float s0[64];
            if (wg == 1) bar_sync(2, 256);
            mbar_wait(bar_full, 0);
            TRC(true, 16 + 48 * wg);
            WG_FENCE();
            gemm_qk(s0, q, dk0);
            WG_COMMIT();
            {
                bar_sync(6 + wg, 128);
                const int t = threadIdx.x & 127;
                asm volatile("st.shared.v4.u32 [%0], {%1,%1,%1,%1};" ::"r"(sbase + kSmemVOff + wg * kVSlotBytes + 32768 + (t >> 3) * 1024 + (t & 7) * 144),
                             "r"(0x3F803F80u) : "memory");
                asm volatile("fence.proxy.async.shared::cta;" ::: "memory");
                __syncwarp();
                if (rel) mbar_arrive_cluster(rel_addr + 8 * (2 + wg));
            }
            wg_wait<0>();
            fence_regs(s0);
            bar_arrive(id_other, 256);
            if (rel) mbar_arrive_cluster(rel_addr);
            sched_boundary(p.zero[4]);
            row_max(s0, ms0, ms1);
            ms0 *= kScale; ms1 *= kScale;
            exp_tile<0, EQK>(s0, ms0, ms1);
            if (wg == 0) exp_tile<EQK, 16>(s0, ms0, ms1);
            mbar_wait(bar_full + 8, 0);
            bar_sync(id_mine, 256);
            TRC(true, 17 + 48 * wg);
            WG_FENCE();
            gemm_qk(s, q, dk0 + (kTileBytes >> 4));
            WG_COMMIT();
            if (wg == 1) exp_tile<EQK, 16>(s0, ms0, ms1);
            pack_tile(pr, s0);
        }
#pragma unroll
        for (int i = 0; i < kON; i++) o[i] = 0.f;

        uint64_t dk = dk0, dv = dv0;
        auto finish = [&](int j, int ks, int vs, uint32_t vpar, uint32_t z) {
            mbar_wait(bar_full + 16 + 8 * vs, vpar);
            fence_regs(o); fence_regs(pr);
            WG_FENCE();
            gemm_pv(o, pr, dv + vs * (kVSlotBytes >> 4));
            WG_COMMIT();
            bar_arrive(id_other, 256);
            wg_wait<1>();
            TRC(TRACE_FULL || j <= 4 || (ks == 1 && wg == 0), 32 + 48 * wg + j);
            fence_regs(s);
            if (rel) mbar_arrive_cluster(rel_addr + 8 * ks);
            exp_tile<0, ESPLIT>(s, ms0, ms1);
            sched_boundary(z);
            wg_wait<0>();
            fence_regs(o); fence_regs(s);
            if (rel) mbar_arrive_cluster(rel_addr + 16 + 8 * vs);
            exp_tile<ESPLIT, 16>(s, ms0, ms1);
            pack_tile(pr, s);
        };
        auto step = [&](int j, int ks, int vs, uint32_t kpar, uint32_t vpar, uint32_t z) {
            mbar_wait(bar_full + 8 * ks, kpar);
            bar_sync(id_mine, 256);
            TRC(TRACE_FULL || j <= 4, 16 + 48 * wg + j);
            fence_regs(s);
            WG_FENCE();
            gemm_qk(s, q, dk + ks * (kTileBytes >> 4));
            WG_COMMIT();
            finish(j, ks, vs, vpar, z);
        };
        finish(1, 1, 0, 0, p.zero[2]);
#pragma unroll 1
        for (int i = 1; i < 8; i++) {
            step(2 * i, 0, 1, i, i + 1, p.zero[0]);
            step(2 * i + 1, 1, 0, i, i, p.zero[1]);
            dk += p.zero[0]; dv += p.zero[0];
        }
        asm volatile("barrier.cluster.arrive.relaxed.aligned;" ::: "memory");

        __nv_bfloat16* op = p.out + (h * kS + qt * 128 + warp * 16 + g) * kD + 8 * c;
        bool ok;
        {
            float hi[36], lo[32];
            const float fz = __uint_as_float(p.zero[1]);
#pragma unroll
            for (int i = 0; i < 36; i++) hi[i] = o[32 + i] + fz;
#pragma unroll
            for (int i = 0; i < 32; i++) lo[i] = o[i] + fz;
            if (wg == 0) bar_sync(1, 256);
            mbar_wait(bar_full + 24, 1);
            fence_regs(hi); fence_regs(lo); fence_regs(pr);
            WG_FENCE();
            const uint64_t d = dv0 + (kVSlotBytes >> 4);
#pragma unroll
            for (int kk = 0; kk < 8; kk++) wgmma_pv_hi(hi, pr[4 * kk], pr[4 * kk + 1], pr[4 * kk + 2], pr[4 * kk + 3], d + ((kk * 2048 + 16384) >> 4));
            WG_COMMIT();
#pragma unroll
            for (int kk = 0; kk < 8; kk++) wgmma_pv_lo(lo, pr[4 * kk], pr[4 * kk + 1], pr[4 * kk + 2], pr[4 * kk + 3], d + ((kk * 2048) >> 4));
            WG_COMMIT();
            wg_wait<1>();
            fence_regs(hi);
            const float i0 = rcp(hi[32]), i1 = rcp(hi[34]);
            uint4 u[4], v[4];
            store_half(op + 64, u, hi, 0, i0, i1);
            sched_boundary(p.zero[5]);
            wg_wait<0>();
            TRC(true, 4 + wg);
            fence_regs(lo);
            store_half(op, v, lo, 0, i0, i1);
            sched_boundary(p.zero[6]);
            ok = all_finite(u, v, __shfl_sync(0xffffffffu, 0u, lane)) && hi[32] <= 1.2379400e27f && hi[34] <= 1.2379400e27f;
        }

        if (bar_red_or(3, 256, !ok)) {
            float m0 = -INFINITY, m1 = -INFINITY;
#pragma unroll
            for (int i = 0; i < kON; i++) o[i] = 0.f;
            const uint8_t* src = g_scratch + (size_t)h * kItems * kTileBytes;
#pragma unroll 1
            for (int j = 0; j < 16; j++) {
                if (threadIdx.x == 0) {
                    mbar_expect_tx(bar_fb, 2 * kTileBytes);
                    bulk_g2s(sbase, src + (size_t)(j == 0 ? 0 : 2 * j - 1) * kTileBytes, kTileBytes, bar_fb);
                    bulk_g2s(sbase + kSmemVOff, src + (size_t)(2 * j + 2) * kTileBytes, kTileBytes, bar_fb);
                }
                mbar_wait(bar_fb, j & 1);
                fence_regs(s);
                WG_FENCE();
                gemm_qk(s, q, dk0);
                WG_COMMIT();
                wg_wait<0>();
                fence_regs(s);
                float a0, a1;
                row_max(s, a0, a1);
                a0 = fmaxf(a0, m0); a1 = fmaxf(a1, m1);
                const float r0 = a0 == -INFINITY ? 0.f : a0, r1 = a1 == -INFINITY ? 0.f : a1;
                const float al0 = ex2((m0 - r0) * kScale), al1 = ex2((m1 - r1) * kScale);
                m0 = a0; m1 = a1;
                exp_tile<0, 16>(s, r0 * kScale, r1 * kScale);
                pack_tile(pr, s);
#pragma unroll
                for (int n = 0; n < kON / 4; n++) { o[4 * n] *= al0; o[4 * n + 1] *= al0; o[4 * n + 2] *= al1; o[4 * n + 3] *= al1; }
                fence_regs(o); fence_regs(pr);
                WG_FENCE();
                gemm_pv(o, pr, dv0);
                WG_COMMIT();
                wg_wait<0>();
                fence_regs(o);
                bar_sync(3, 256);
            }
            uint4 v[4];
            store_half(op, v, o, 0, 1.f / o[64], 1.f / o[66]);
            store_half(op + 64, v, o, 32, 1.f / o[64], 1.f / o[66]);
        }
        asm volatile("barrier.cluster.wait.aligned;" ::: "memory");
    }
}

}

extern "C" void kernel_launch(void* const* d_in, const int* in_sizes, int n_in, void* d_out, int out_size) {
    (void)in_sizes; (void)n_in; (void)out_size;
    Params p;
    p.q = (const __nv_bfloat16*)d_in[0];
    p.qk = (const int*)d_in[1];
    p.k_scales = (const __nv_bfloat16*)d_in[2];
    p.k_zeros = (const __nv_bfloat16*)d_in[3];
    p.qv = (const int*)d_in[4];
    p.v_scales = (const __nv_bfloat16*)d_in[5];
    p.v_zeros = (const __nv_bfloat16*)d_in[6];
    p.q_cos = (const __nv_bfloat16*)d_in[7];
    p.q_sin = (const __nv_bfloat16*)d_in[8];
    p.k_cos = (const __nv_bfloat16*)d_in[9];
    p.k_sin = (const __nv_bfloat16*)d_in[10];
    p.out = (__nv_bfloat16*)d_out;
    for (int i = 0; i < 7; i++) p.zero[i] = 0;
    p.t_v0 = 800; p.t_q = 400; p.dt_q = 630; p.t_next = 5900; p.dt_next = 400; p.t_k2 = 2800; p.gap_q = 200; p.k_v1 = 6;
    p.t_poll = 2200; p.stagger = 60; p.lag_q = 110; p.catch_q = 24;
    static int co_resident = -1;
    if (co_resident < 0) {
        cudaFuncSetAttribute(attn_kernel, cudaFuncAttributeMaxDynamicSharedMemorySize, kSmemBytes);
        cudaLaunchConfig_t cfg = {};
        cfg.gridDim = dim3(kH * 16); cfg.blockDim = dim3(384); cfg.dynamicSmemBytes = kSmemBytes;
        cudaLaunchAttribute at;
        at.id = cudaLaunchAttributeClusterDimension;
        at.val.clusterDim.x = 2; at.val.clusterDim.y = 1; at.val.clusterDim.z = 1;
        cfg.attrs = &at; cfg.numAttrs = 1;
        int clusters = 0;
        co_resident = cudaOccupancyMaxActiveClusters(&clusters, attn_kernel, &cfg) == cudaSuccess && clusters >= kH * 8;
        (void)cudaGetLastError();
    }
    if (!co_resident) prefill_kernel<<<kItems * kH * 16, 128>>>(p);
    attn_kernel<<<kH * 16, 384, kSmemBytes>>>(p);
}
```

```cpp
#include <cuda_runtime.h>
#include <cuda_bf16.h>
#include <stdint.h>

namespace {

constexpr int kH = 8, kS = 2048, kD = 128;
constexpr int kItems = 33;
constexpr int kTileBytes = 32768;
constexpr int kVSlotBytes = 49152;
constexpr int kDqWarps = 3;
constexpr int kRawBytes = 12288;
constexpr int kSmemVOff = 2 * kTileBytes;
constexpr int kSmemRawOff = kSmemVOff + 2 * kVSlotBytes;
constexpr int kSmemOutOff = kSmemRawOff + kDqWarps * kRawBytes;
constexpr int kSmemScOff = kSmemOutOff + kDqWarps * 2048;
constexpr int kSmemBarOff = kSmemScOff + kDqWarps * 768;
constexpr int kSmemBytes = kSmemBarOff + 512 + 1024;
constexpr int kFlagStride = 64;
constexpr int kON = 68;
constexpr float kScale = 0.08838834764831845f * 1.4426950408889634f;
constexpr uint32_t kWaitLimit = 1u << 30;
constexpr int kExpSplit = 9;
constexpr int kExpSplit0 = 10;

__device__ __align__(1024) uint8_t g_scratch[(size_t)kH * kItems * kTileBytes];
__device__ __align__(256) unsigned g_flags[kH * kItems * kFlagStride];
__device__ unsigned g_done;

#define TRX TR

struct Params {
    const __nv_bfloat16* q;
    const int* qk;
    const __nv_bfloat16* k_scales;
    const __nv_bfloat16* k_zeros;
    const int* qv;
    const __nv_bfloat16* v_scales;
    const __nv_bfloat16* v_zeros;
    const __nv_bfloat16* q_cos;
    const __nv_bfloat16* q_sin;
    const __nv_bfloat16* k_cos;
    const __nv_bfloat16* k_sin;
    __nv_bfloat16* out;
    uint32_t zero[8];
    int t_v0, t_q, dt_q, t_next, dt_next, t_k2, gap_q, k_v1, t_poll, stagger, lag_q, catch_q;
};

__device__ __forceinline__ uint32_t smem_u32(const void* p) { return (uint32_t)__cvta_generic_to_shared(p); }
__device__ __forceinline__ uint32_t clock32() {
    uint32_t c;
    asm volatile("mov.u32 %0, %%clock;" : "=r"(c));
    return c;
}
__device__ __forceinline__ void wait_until(uint32_t t0, int t) {
    while ((int)(clock32() - t0) < t) {}
    __syncwarp();
}
__device__ __forceinline__ bool elect() {
    uint32_t r;
    asm volatile("{\n.reg .pred p;\nelect.sync _|p, 0xffffffff;\nselp.u32 %0, 1, 0, p;\n}\n" : "=r"(r));
    return r != 0;
}
__device__ __forceinline__ void mbar_init(uint32_t bar, uint32_t count) {
    asm volatile("mbarrier.init.shared::cta.b64 [%0], %1;" ::"r"(bar), "r"(count) : "memory");
}
__device__ __forceinline__ void mbar_expect_tx(uint32_t bar, uint32_t bytes) {
    asm volatile("mbarrier.arrive.expect_tx.shared::cta.b64 _, [%0], %1;" ::"r"(bar), "r"(bytes) : "memory");
}
__device__ __forceinline__ bool mbar_try(uint32_t bar, uint32_t parity) {
    uint32_t ok;
    asm volatile(
        "{\n.reg .pred p;\n"
        "mbarrier.try_wait.parity.shared::cta.b64 p, [%1], %2;\n"
        "selp.u32 %0, 1, 0, p;\n}\n"
        : "=r"(ok)
        : "r"(bar), "r"(parity)
        : "memory");
    return ok != 0;
}
__device__ __forceinline__ void mbar_wait(uint32_t bar, uint32_t parity) {
    if (mbar_try(bar, parity)) return;
    const uint32_t t0 = clock32();
    while (!mbar_try(bar, parity)) {
        if (clock32() - t0 > kWaitLimit) break;
    }
}
__device__ __forceinline__ void mbar_wait_idle(uint32_t bar, uint32_t parity) {
    if (mbar_try(bar, parity)) return;
    const uint32_t t0 = clock32();
    uint32_t ok;
    do {
        asm volatile(
            "{\n.reg .pred p;\n"
            "mbarrier.try_wait.parity.shared::cta.b64 p, [%1], %2, 20000;\n"
            "selp.u32 %0, 1, 0, p;\n}\n"
            : "=r"(ok)
            : "r"(bar), "r"(parity)
            : "memory");
    } while (!ok && clock32() - t0 <= kWaitLimit);
    __syncwarp();
}
__device__ __forceinline__ void mbar_arrive_cluster(uint32_t cluster_addr) {
    asm volatile("mbarrier.arrive.shared::cluster.b64 _, [%0];" ::"r"(cluster_addr) : "memory");
}
__device__ __forceinline__ uint32_t mapa(uint32_t addr, uint32_t rank) {
    uint32_t r;
    asm("mapa.shared::cluster.u32 %0, %1, %2;" : "=r"(r) : "r"(addr), "r"(rank));
    return r;
}
__device__ __forceinline__ void bulk_g2s(uint32_t dst, const void* src, uint32_t bytes, uint32_t bar) {
    asm volatile("cp.async.bulk.shared::cluster.global.mbarrier::complete_tx::bytes [%0], [%1], %2, [%3];" ::"r"(dst),
                 "l"(src), "r"(bytes), "r"(bar)
                 : "memory");
}
__device__ __forceinline__ void bulk_g2s_mc(uint32_t dst, const void* src, uint32_t bytes, uint32_t bar, uint16_t mask) {
    asm volatile(
        "cp.async.bulk.shared::cluster.global.mbarrier::complete_tx::bytes.multicast::cluster [%0], [%1], %2, [%3], %4;" ::"r"(dst),
        "l"(src), "r"(bytes), "r"(bar), "h"(mask)
        : "memory");
}
__device__ __forceinline__ void bar_sync(int id, int n) { asm volatile("bar.sync %0, %1;" ::"r"(id), "r"(n) : "memory"); }
__device__ __forceinline__ void bar_arrive(int id, int n) { asm volatile("bar.arrive %0, %1;" ::"r"(id), "r"(n) : "memory"); }
__device__ __forceinline__ bool bar_red_or(int id, int n, bool v) {
    uint32_t r;
    asm volatile(
        "{\n.reg .pred p, q;\nsetp.ne.u32 q, %3, 0;\n"
        "bar.red.or.pred p, %1, %2, q;\nselp.u32 %0, 1, 0, p;\n}\n"
        : "=r"(r)
        : "r"(id), "r"(n), "r"((uint32_t)v)
        : "memory");
    return r != 0;
}
__device__ __forceinline__ void sched_boundary(uint32_t zero) {
    asm volatile("{\n.reg .pred p;\nsetp.ne.u32 p, %0, 0;\n@p exit;\n}\n" ::"r"(zero) : "memory");
}
__device__ __forceinline__ float ex2(float x) {
    float y;
    asm("ex2.approx.ftz.f32 %0, %1;" : "=f"(y) : "f"(x));
    return y;
}
__device__ __forceinline__ float rcp(float x) {
    float y;
    asm("rcp.approx.ftz.f32 %0, %1;" : "=f"(y) : "f"(x));
    return y;
}
__device__ __forceinline__ uint32_t pack_bf16(float lo, float hi) {
    uint32_t r;
    asm("cvt.rn.bf16x2.f32 %0, %1, %2;" : "=r"(r) : "f"(hi), "f"(lo));
    return r;
}
__device__ __forceinline__ uint32_t hmul2(uint32_t a, uint32_t b) {
    uint32_t r;
    asm("mul.rn.bf16x2 %0, %1, %2;" : "=r"(r) : "r"(a), "r"(b));
    return r;
}
__device__ __forceinline__ uint32_t hadd2(uint32_t a, uint32_t b) {
    uint32_t r;
    asm("add.rn.bf16x2 %0, %1, %2;" : "=r"(r) : "r"(a), "r"(b));
    return r;
}
__device__ __forceinline__ uint32_t hsub2(uint32_t a, uint32_t b) {
    uint32_t r;
    asm("sub.rn.bf16x2 %0, %1, %2;" : "=r"(r) : "r"(a), "r"(b));
    return r;
}
__device__ __forceinline__ uint32_t hfma2(uint32_t a, uint32_t b, uint32_t c) {
    uint32_t r;
    asm("fma.rn.bf16x2 %0, %1, %2, %3;" : "=r"(r) : "r"(a), "r"(b), "r"(c));
    return r;
}
__device__ __forceinline__ uint4 lds128(uint32_t a) {
    uint4 v;
    asm volatile("ld.shared.v4.u32 {%0,%1,%2,%3}, [%4];" : "=r"(v.x), "=r"(v.y), "=r"(v.z), "=r"(v.w) : "r"(a));
    return v;
}
__device__ __forceinline__ uint2 lds64(uint32_t a) {
    uint2 v;
    asm volatile("ld.shared.v2.u32 {%0,%1}, [%2];" : "=r"(v.x), "=r"(v.y) : "r"(a));
    return v;
}
__device__ __forceinline__ uint32_t lds32(uint32_t a) {
    uint32_t v;
    asm volatile("ld.shared.u32 %0, [%1];" : "=r"(v) : "r"(a));
    return v;
}
__device__ __forceinline__ void sts32(uint32_t a, uint32_t v) { asm volatile("st.shared.u32 [%0], %1;" ::"r"(a), "r"(v) : "memory"); }
__device__ __forceinline__ uint4 ldg128(const void* p) {
    uint4 v;
    asm volatile("ld.global.nc.L1::no_allocate.v4.u32 {%0,%1,%2,%3}, [%4];" : "=r"(v.x), "=r"(v.y), "=r"(v.z), "=r"(v.w) : "l"(p) : "memory");
    return v;
}
__device__ __forceinline__ uint2 ldg64(const void* p) {
    uint2 v;
    asm volatile("ld.global.nc.L1::no_allocate.v2.u32 {%0,%1}, [%2];" : "=r"(v.x), "=r"(v.y) : "l"(p) : "memory");
    return v;
}
__device__ __forceinline__ uint32_t ldg32(const void* p) {
    uint32_t v;
    asm volatile("ld.global.nc.L1::no_allocate.u32 %0, [%1];" : "=r"(v) : "l"(p) : "memory");
    return v;
}
__device__ __forceinline__ uint32_t ld_gpu(const void* p) {
    uint32_t v;
    asm volatile("ld.relaxed.gpu.global.u32 %0, [%1];" : "=r"(v) : "l"(p) : "memory");
    return v;
}
__device__ __forceinline__ void red_gpu(unsigned* p, uint32_t v) {
    asm volatile("red.relaxed.gpu.global.add.u32 [%0], %1;" ::"l"(p), "r"(v) : "memory");
}

#define WG_FENCE() asm volatile("wgmma.fence.sync.aligned;" ::: "memory")
#define WG_COMMIT() asm volatile("wgmma.commit_group.sync.aligned;" ::: "memory")
template <int N>
__device__ __forceinline__ void wg_wait() {
    asm volatile("wgmma.wait_group.sync.aligned %0;" ::"n"(N) : "memory");
}
template <int ACC>
__device__ __forceinline__ void wgmma_qk(float (&d)[64], uint32_t a0, uint32_t a1, uint32_t a2, uint32_t a3, uint64_t db) {
    asm volatile(
        "{\n.reg .pred p;\nsetp.ne.b32 p, %69, 0;\n"
        "wgmma.mma_async.sync.aligned.m64n128k16.f32.bf16.bf16 "
        "{%0,%1,%2,%3,%4,%5,%6,%7,%8,%9,%10,%11,%12,%13,%14,%15,%16,%17,%18,%19,%20,%21,%22,%23,"
        "%24,%25,%26,%27,%28,%29,%30,%31,%32,%33,%34,%35,%36,%37,%38,%39,%40,%41,%42,%43,%44,%45,%46,%47,"
        "%48,%49,%50,%51,%52,%53,%54,%55,%56,%57,%58,%59,%60,%61,%62,%63}, {%64,%65,%66,%67}, %68, p, 1, 1, 0;\n}\n"
        : "+f"(d[0]), "+f"(d[1]), "+f"(d[2]), "+f"(d[3]), "+f"(d[4]), "+f"(d[5]), "+f"(d[6]), "+f"(d[7]),
          "+f"(d[8]), "+f"(d[9]), "+f"(d[10]), "+f"(d[11]), "+f"(d[12]), "+f"(d[13]), "+f"(d[14]), "+f"(d[15]),
          "+f"(d[16]), "+f"(d[17]), "+f"(d[18]), "+f"(d[19]), "+f"(d[20]), "+f"(d[21]), "+f"(d[22]), "+f"(d[23]),
          "+f"(d[24]), "+f"(d[25]), "+f"(d[26]), "+f"(d[27]), "+f"(d[28]), "+f"(d[29]), "+f"(d[30]), "+f"(d[31]),
          "+f"(d[32]), "+f"(d[33]), "+f"(d[34]), "+f"(d[35]), "+f"(d[36]), "+f"(d[37]), "+f"(d[38]), "+f"(d[39]),
          "+f"(d[40]), "+f"(d[41]), "+f"(d[42]), "+f"(d[43]), "+f"(d[44]), "+f"(d[45]), "+f"(d[46]), "+f"(d[47]),
          "+f"(d[48]), "+f"(d[49]), "+f"(d[50]), "+f"(d[51]), "+f"(d[52]), "+f"(d[53]), "+f"(d[54]), "+f"(d[55]),
          "+f"(d[56]), "+f"(d[57]), "+f"(d[58]), "+f"(d[59]), "+f"(d[60]), "+f"(d[61]), "+f"(d[62]), "+f"(d[63])
        : "r"(a0), "r"(a1), "r"(a2), "r"(a3), "l"(db), "n"(ACC));
}
__device__ __forceinline__ void wgmma_pv(float (&d)[kON], uint32_t a0, uint32_t a1, uint32_t a2, uint32_t a3, uint64_t db) {
    asm volatile(
        "wgmma.mma_async.sync.aligned.m64n136k16.f32.bf16.bf16 "
        "{%0,%1,%2,%3,%4,%5,%6,%7,%8,%9,%10,%11,%12,%13,%14,%15,%16,%17,%18,%19,%20,%21,%22,%23,"
        "%24,%25,%26,%27,%28,%29,%30,%31,%32,%33,%34,%35,%36,%37,%38,%39,%40,%41,%42,%43,%44,%45,%46,%47,"
        "%48,%49,%50,%51,%52,%53,%54,%55,%56,%57,%58,%59,%60,%61,%62,%63,%64,%65,%66,%67}, {%68,%69,%70,%71}, %72, 1, 1, 1, 1;\n"
        : "+f"(d[0]), "+f"(d[1]), "+f"(d[2]), "+f"(d[3]), "+f"(d[4]), "+f"(d[5]), "+f"(d[6]), "+f"(d[7]),
          "+f"(d[8]), "+f"(d[9]), "+f"(d[10]), "+f"(d[11]), "+f"(d[12]), "+f"(d[13]), "+f"(d[14]), "+f"(d[15]),
          "+f"(d[16]), "+f"(d[17]), "+f"(d[18]), "+f"(d[19]), "+f"(d[20]), "+f"(d[21]), "+f"(d[22]), "+f"(d[23]),
          "+f"(d[24]), "+f"(d[25]), "+f"(d[26]), "+f"(d[27]), "+f"(d[28]), "+f"(d[29]), "+f"(d[30]), "+f"(d[31]),
          "+f"(d[32]), "+f"(d[33]), "+f"(d[34]), "+f"(d[35]), "+f"(d[36]), "+f"(d[37]), "+f"(d[38]), "+f"(d[39]),
          "+f"(d[40]), "+f"(d[41]), "+f"(d[42]), "+f"(d[43]), "+f"(d[44]), "+f"(d[45]), "+f"(d[46]), "+f"(d[47]),
          "+f"(d[48]), "+f"(d[49]), "+f"(d[50]), "+f"(d[51]), "+f"(d[52]), "+f"(d[53]), "+f"(d[54]), "+f"(d[55]),
          "+f"(d[56]), "+f"(d[57]), "+f"(d[58]), "+f"(d[59]), "+f"(d[60]), "+f"(d[61]), "+f"(d[62]), "+f"(d[63]),
          "+f"(d[64]), "+f"(d[65]), "+f"(d[66]), "+f"(d[67])
        : "r"(a0), "r"(a1), "r"(a2), "r"(a3), "l"(db));
}
__device__ __forceinline__ void wgmma_pv_hi(float (&d)[36], uint32_t a0, uint32_t a1, uint32_t a2, uint32_t a3, uint64_t db) {
    asm volatile(
        "wgmma.mma_async.sync.aligned.m64n72k16.f32.bf16.bf16 "
        "{%0,%1,%2,%3,%4,%5,%6,%7,%8,%9,%10,%11,%12,%13,%14,%15,%16,%17,%18,%19,%20,%21,%22,%23,"
        "%24,%25,%26,%27,%28,%29,%30,%31,%32,%33,%34,%35}, {%36,%37,%38,%39}, %40, 1, 1, 1, 1;\n"
        : "+f"(d[0]), "+f"(d[1]), "+f"(d[2]), "+f"(d[3]), "+f"(d[4]), "+f"(d[5]), "+f"(d[6]), "+f"(d[7]),
          "+f"(d[8]), "+f"(d[9]), "+f"(d[10]), "+f"(d[11]), "+f"(d[12]), "+f"(d[13]), "+f"(d[14]), "+f"(d[15]),
          "+f"(d[16]), "+f"(d[17]), "+f"(d[18]), "+f"(d[19]), "+f"(d[20]), "+f"(d[21]), "+f"(d[22]), "+f"(d[23]),
          "+f"(d[24]), "+f"(d[25]), "+f"(d[26]), "+f"(d[27]), "+f"(d[28]), "+f"(d[29]), "+f"(d[30]), "+f"(d[31]),
          "+f"(d[32]), "+f"(d[33]), "+f"(d[34]), "+f"(d[35])
        : "r"(a0), "r"(a1), "r"(a2), "r"(a3), "l"(db));
}
__device__ __forceinline__ void wgmma_pv_lo(float (&d)[32], uint32_t a0, uint32_t a1, uint32_t a2, uint32_t a3, uint64_t db) {
    asm volatile(
        "wgmma.mma_async.sync.aligned.m64n64k16.f32.bf16.bf16 "
        "{%0,%1,%2,%3,%4,%5,%6,%7,%8,%9,%10,%11,%12,%13,%14,%15,%16,%17,%18,%19,%20,%21,%22,%23,"
        "%24,%25,%26,%27,%28,%29,%30,%31}, {%32,%33,%34,%35}, %36, 1, 1, 1, 1;\n"
        : "+f"(d[0]), "+f"(d[1]), "+f"(d[2]), "+f"(d[3]), "+f"(d[4]), "+f"(d[5]), "+f"(d[6]), "+f"(d[7]),
          "+f"(d[8]), "+f"(d[9]), "+f"(d[10]), "+f"(d[11]), "+f"(d[12]), "+f"(d[13]), "+f"(d[14]), "+f"(d[15]),
          "+f"(d[16]), "+f"(d[17]), "+f"(d[18]), "+f"(d[19]), "+f"(d[20]), "+f"(d[21]), "+f"(d[22]), "+f"(d[23]),
          "+f"(d[24]), "+f"(d[25]), "+f"(d[26]), "+f"(d[27]), "+f"(d[28]), "+f"(d[29]), "+f"(d[30]), "+f"(d[31])
        : "r"(a0), "r"(a1), "r"(a2), "r"(a3), "l"(db));
}
template <int N>
__device__ __forceinline__ void fence_regs(float (&d)[N]) {
#pragma unroll
    for (int i = 0; i < N; i++) asm volatile("" : "+f"(d[i])::"memory");
}
__device__ __forceinline__ void fence_regs(uint32_t (&d)[32]) {
#pragma unroll
    for (int i = 0; i < 32; i++) asm volatile("" : "+r"(d[i])::"memory");
}
constexpr uint64_t kDescK = (uint64_t(1) << 62) | (uint64_t(1024 >> 4) << 32) | (uint64_t(1) << 16);
constexpr uint64_t kDescV = (uint64_t(1) << 62) | (uint64_t(1024 >> 4) << 32) | (uint64_t(16384 >> 4) << 16);

__device__ __forceinline__ void gemm_qk(float (&s)[64], const uint32_t (&q)[32], uint64_t d) {
    wgmma_qk<0>(s, q[0], q[1], q[2], q[3], d);
#pragma unroll
    for (int kk = 1; kk < 8; kk++)
        wgmma_qk<1>(s, q[4 * kk], q[4 * kk + 1], q[4 * kk + 2], q[4 * kk + 3], d + (((kk >> 2) * 16384 + (kk & 3) * 32) >> 4));
}
__device__ __forceinline__ void gemm_pv(float (&o)[kON], const uint32_t (&p)[32], uint64_t d) {
#pragma unroll
    for (int kk = 0; kk < 8; kk++) wgmma_pv(o, p[4 * kk], p[4 * kk + 1], p[4 * kk + 2], p[4 * kk + 3], d + ((kk * 2048) >> 4));
}

__device__ __forceinline__ void dequant4(uint32_t (&v)[4], uint32_t sc, uint32_t zp) {
    const uint32_t s0 = __byte_perm(sc, 0, 0x1010), s1 = __byte_perm(sc, 0, 0x3232);
    const uint32_t z0 = __byte_perm(zp, 0, 0x1010), z1 = __byte_perm(zp, 0, 0x3232);
    v[0] = hmul2(hsub2(v[0], z0), s0); v[1] = hmul2(hsub2(v[1], z0), s0);
    v[2] = hmul2(hsub2(v[2], z1), s1); v[3] = hmul2(hsub2(v[3], z1), s1);
}
__device__ __forceinline__ void to_bf16(uint32_t (&v)[4], const uint4& lo, const uint4& hi) {
    v[0] = pack_bf16((float)(int)lo.x, (float)(int)lo.y); v[1] = pack_bf16((float)(int)lo.z, (float)(int)lo.w);
    v[2] = pack_bf16((float)(int)hi.x, (float)(int)hi.y); v[3] = pack_bf16((float)(int)hi.z, (float)(int)hi.w);
}
__device__ __forceinline__ void rope4(uint32_t (&v)[4], const uint2& cl, const uint2& ch, const uint2& sl, const uint2& sh) {
    const uint32_t r0 = hsub2(hmul2(v[0], cl.x), hmul2(v[2], sl.x)), r1 = hsub2(hmul2(v[1], cl.y), hmul2(v[3], sl.y));
    const uint32_t r2 = hadd2(hmul2(v[2], ch.x), hmul2(v[0], sh.x)), r3 = hadd2(hmul2(v[3], ch.y), hmul2(v[1], sh.y));
    v[0] = r0; v[1] = r1; v[2] = r2; v[3] = r3;
}

template <bool IS_V>
__device__ __forceinline__ void dequant_slice(uint32_t ia, uint32_t ca, uint32_t oa, uint32_t sc, uint32_t zp) {
    uint4 lo = lds128(ia), hi = lds128(ia + 256);
#pragma unroll
    for (int it = 0; it < 4; it++) {
        uint2 cl, ch, sl, sh;
        if (!IS_V) {
            const uint32_t a = ca ^ ((it >> 1) * 64 + (it & 1) * 8);
            cl = lds64(a); sl = lds64(a + 2048); ch = lds64(a + 128); sh = lds64(a + 2048 + 128);
        }
        uint32_t v[4];
        to_bf16(v, lo, hi);
        if (it < 3) {
            const uint32_t a = ia ^ (((it + 1) >> 1) * 128 + ((it + 1) & 1) * 16);
            lo = lds128(a); hi = lds128(a + 256);
        }
        dequant4(v, sc, zp);
        if (!IS_V) rope4(v, cl, ch, sl, sh);
        const uint32_t o0 = oa ^ (it << 5), o1 = oa ^ ((it << 5) | 16);
        sts32(o0, v[0]); sts32(o1, v[1]); sts32(o0 + 1024, v[2]); sts32(o1 + 1024, v[3]);
    }
}

struct RowsIn { uint4 lo, hi; uint2 cl, ch, sl, sh; uint32_t sc, zp; };
template <bool IS_V>
__device__ __forceinline__ void rows_load(RowsIn& x, const Params& p, int h, int row, int mp) {
    const int hr = h * kS + row;
    const int* ints = (IS_V ? p.qv : p.qk) + hr * kD + 4 * mp;
    x.lo = ldg128(ints); x.hi = ldg128(ints + 64);
    if (!IS_V) {
        x.cl = ldg64(p.k_cos + row * kD + 4 * mp); x.ch = ldg64(p.k_cos + row * kD + 64 + 4 * mp);
        x.sl = ldg64(p.k_sin + row * kD + 4 * mp); x.sh = ldg64(p.k_sin + row * kD + 64 + 4 * mp);
    }
    x.sc = ldg32((IS_V ? p.v_scales : p.k_scales) + hr * 2); x.zp = ldg32((IS_V ? p.v_zeros : p.k_zeros) + hr * 2);
}
template <bool IS_V>
__device__ __forceinline__ uint8_t* rows_store(const RowsIn& a, uint8_t* slice, int r, int mp) {
    const int j = mp >> 3, c = (mp >> 1) & 3, b = mp & 1;
    uint32_t v[4];
    to_bf16(v, a.lo, a.hi);
    dequant4(v, a.sc, a.zp);
    if (!IS_V) rope4(v, a.cl, a.ch, a.sl, a.sh);
    const bool c0 = c & 1, c1 = c & 2;
    uint32_t x = __shfl_xor_sync(0xffffffffu, c0 ? v[0] : v[1], 2), y = __shfl_xor_sync(0xffffffffu, c0 ? v[2] : v[3], 2);
    const uint32_t a0 = c0 ? x : v[0], a1 = c0 ? v[1] : x, a2 = c0 ? y : v[2], a3 = c0 ? v[3] : y;
    x = __shfl_xor_sync(0xffffffffu, c1 ? a0 : a2, 4); y = __shfl_xor_sync(0xffffffffu, c1 ? a1 : a3, 4);
    uint8_t* dst = slice + (c >> 1) * 16384 + r * 128 + (((4 * j + 2 * b + (c & 1)) ^ r) << 4);
    *reinterpret_cast<uint4*>(dst) = make_uint4(c1 ? x : a0, c1 ? y : a1, c1 ? a2 : x, c1 ? a3 : y);
    return dst;
}

__global__ void __launch_bounds__(128) prefill_kernel(const __grid_constant__ Params p) {
    const int slice = blockIdx.x & 15, h = (blockIdx.x >> 4) & 7, n = blockIdx.x >> 7;
    if (n == kItems - 2) return;
    const int r = threadIdx.x >> 4, mp = threadIdx.x & 15;
    const bool is_v = n != 0 && !(n & 1);
    const int row = (is_v ? (n >> 1) - 1 : (n + 1) >> 1) * 128 + slice * 8 + r;
    uint8_t* dst = g_scratch + (size_t)(h * kItems + n) * kTileBytes + slice * 1024;
    RowsIn x;
    if (is_v) { rows_load<true>(x, p, h, row, mp); rows_store<true>(x, dst, r, mp); }
    else { rows_load<false>(x, p, h, row, mp); rows_store<false>(x, dst, r, mp); }
    if (threadIdx.x == 0 && slice == 0) g_flags[(h * kItems + n) * kFlagStride] = 16;
}

template <int N0, int N1>
__device__ __forceinline__ void exp_tile(float (&s)[64], float ms0, float ms1) {
    if (N0 == 0) {
#pragma unroll
        for (int i = 0; i < 64; i++) s[i] = fmaf(s[i], kScale, (i & 2) ? -ms1 : -ms0);
    }
#pragma unroll
    for (int i = 4 * N0; i < 4 * N1; i++) s[i] = ex2(s[i]);
}
__device__ __forceinline__ void row_max(const float (&s)[64], float& m0, float& m1) {
    float a0 = fmaxf(s[0], s[1]), a1 = fmaxf(s[2], s[3]), b0 = fmaxf(s[4], s[5]), b1 = fmaxf(s[6], s[7]);
#pragma unroll
    for (int n = 2; n < 16; n += 2) {
        a0 = fmaxf(a0, fmaxf(s[4 * n], s[4 * n + 1])); a1 = fmaxf(a1, fmaxf(s[4 * n + 2], s[4 * n + 3]));
        b0 = fmaxf(b0, fmaxf(s[4 * n + 4], s[4 * n + 5])); b1 = fmaxf(b1, fmaxf(s[4 * n + 6], s[4 * n + 7]));
    }
    m0 = fmaxf(a0, b0); m1 = fmaxf(a1, b1);
    m0 = fmaxf(m0, __shfl_xor_sync(0xffffffffu, m0, 1)); m1 = fmaxf(m1, __shfl_xor_sync(0xffffffffu, m1, 1));
    m0 = fmaxf(m0, __shfl_xor_sync(0xffffffffu, m0, 2)); m1 = fmaxf(m1, __shfl_xor_sync(0xffffffffu, m1, 2));
}
__device__ __forceinline__ void pack_tile(uint32_t (&pr)[32], const float (&s)[64]) {
#pragma unroll
    for (int i = 0; i < 32; i++) pr[i] = pack_bf16(s[2 * i], s[2 * i + 1]);
}
template <int N>
__device__ __forceinline__ void store_half(__nv_bfloat16* op, uint4 (&v)[4], const float (&o)[N], int b, float i0, float i1) {
#pragma unroll
    for (int j = 0; j < 2; j++) {
        uint4 &v0 = v[2 * j], &v1 = v[2 * j + 1];
        const float* x = o + b + 16 * j;
        v0.x = pack_bf16(x[0] * i0, x[1] * i0);  v0.y = pack_bf16(x[4] * i0, x[5] * i0);
        v0.z = pack_bf16(x[8] * i0, x[9] * i0);  v0.w = pack_bf16(x[12] * i0, x[13] * i0);
        *reinterpret_cast<uint4*>(op + 32 * j) = v0;
        v1.x = pack_bf16(x[2] * i1, x[3] * i1);  v1.y = pack_bf16(x[6] * i1, x[7] * i1);
        v1.z = pack_bf16(x[10] * i1, x[11] * i1); v1.w = pack_bf16(x[14] * i1, x[15] * i1);
        *reinterpret_cast<uint4*>(op + 8 * kD + 32 * j) = v1;
    }
}
__device__ __forceinline__ bool all_finite(const uint4 (&u)[4], const uint4 (&v)[4], uint32_t zero) {
    uint32_t a[4] = {0, 0, 0, 0};
#pragma unroll
    for (int j = 0; j < 4; j++) {
        a[0] = hfma2(u[j].x, zero, hfma2(v[j].x, zero, a[0])); a[1] = hfma2(u[j].y, zero, hfma2(v[j].y, zero, a[1]));
        a[2] = hfma2(u[j].z, zero, hfma2(v[j].z, zero, a[2])); a[3] = hfma2(u[j].w, zero, hfma2(v[j].w, zero, a[3]));
    }
    return ((a[0] | a[1] | a[2] | a[3]) & 0x7fff7fffu) == 0;
}

template <bool B> struct Tag { static constexpr bool value = B; };

__global__ void __cluster_dims__(2, 1, 1) __launch_bounds__(384, 1) attn_kernel(const __grid_constant__ Params p) {
    extern __shared__ uint8_t smem_raw[];
    const uint32_t sbase = (smem_u32(smem_raw) + 1023) & ~1023u;
    const uint32_t bar_full = sbase + kSmemBarOff;
    const uint32_t bar_empty = bar_full + 32;
    const uint32_t bar_raw = bar_empty + 32;
    const uint32_t bar_q = bar_raw + 16 * kDqWarps;
    const uint32_t bar_fb = bar_q + 128;

    const int h = blockIdx.x >> 4, qt = blockIdx.x & 15;
    const int warp = __shfl_sync(0xffffffffu, threadIdx.x >> 5, 0), lane = threadIdx.x & 31;

    if (warp >= 8) {
        asm volatile("setmaxnreg.dec.sync.aligned.u32 56;");
        if (warp == 8) {
            const uint32_t t0 = clock32();
            const unsigned* fp = g_flags + (h * kItems + lane) * kFlagStride;
            uint32_t early = 0;
            if (lane < 8) early = ld_gpu(fp);
            if (elect()) {
                for (int i = 0; i < 4; i++) {
                    mbar_init(bar_full + 8 * i, 1);
                    mbar_init(bar_empty + 8 * i, 16);
                }
                mbar_init(bar_fb, 1);
                asm volatile("fence.mbarrier_init.release.cluster;" ::: "memory");
            }
            __syncwarp();
            asm volatile("barrier.cluster.arrive.relaxed.aligned;" ::: "memory");
            asm volatile("barrier.cluster.wait.acquire.aligned;" ::: "memory");
            const uint32_t rank = blockIdx.x & 1;
            const uint8_t* src = g_scratch + (size_t)h * kItems * kTileBytes + rank * (kTileBytes / 2);
            uint32_t ready = __ballot_sync(0xffffffffu, early >= 16);
            asm volatile("fence.acquire.gpu;" ::: "memory");
            uint32_t parity = 3;
            wait_until(t0, p.t_poll);
#pragma unroll 1
            for (int n = 0; n < kItems; n++, ready >>= 1, src += kTileBytes, fp += kFlagStride) {
                if (n == kItems - 2) continue;
                const bool mine = lane < 2 && n + lane < kItems;
                if (!(ready & 1)) {
                    const uint32_t t1 = clock32();
                    do {
                        ready = __ballot_sync(0xffffffffu, mine && ld_gpu(fp) >= 16);
                    } while (!(ready & 1) && !__any_sync(0xffffffffu, clock32() - t1 > kWaitLimit));
                    asm volatile("fence.acquire.gpu;" ::: "memory");
                }
                const bool is_v = n != 0 && !(n & 1);
                const int odd = (((n + 1) >> 1) & 1) ^ (is_v ? 1 : 0);
                const int slot = (is_v ? 2 : 0) + odd;
                const bool peek = !(ready & 2);
                uint32_t ahead = 0;
                if (peek && mine) ahead = ld_gpu(fp);
                mbar_wait_idle(bar_empty + 8 * slot, (parity >> slot) & 1);
                if (elect()) {
                    mbar_expect_tx(bar_full + 8 * slot, kTileBytes);
                    const uint32_t dst = sbase + (is_v ? kSmemVOff + odd * kVSlotBytes : odd * kTileBytes);
                    bulk_g2s_mc(dst + rank * (kTileBytes / 2), src, kTileBytes / 2, bar_full + 8 * slot, (uint16_t)3);
                }
                parity ^= 1u << slot;
                if (peek) {
                    ready = __ballot_sync(0xffffffffu, ahead >= 16);
                    asm volatile("fence.acquire.gpu;" ::: "memory");
                }
            }
            uint32_t ticket = 0;
            if (lane == 0) ticket = atomicAdd(&g_done, 1u);
            if (__shfl_sync(0xffffffffu, ticket, 0) == gridDim.x - 1) {
                for (int i = lane; i < kH * kItems; i += 32) g_flags[i * kFlagStride] = 0;
                if (lane == 0) g_done = 0;
            }
        } else {
            const int w = warp - 9;
            const uint32_t t0 = clock32() + p.stagger * h;
            const int first = w == 0 ? 2 : 5 - w;
            const int last = first == 4 ? 28 : kItems - 1;
            const uint32_t my_bar = bar_raw + 16 * w;
            const uint32_t my_raw = sbase + kSmemRawOff + w * kRawBytes;
            const uint32_t my_out = sbase + kSmemOutOff + w * 2048;
            const uint32_t my_sc = sbase + kSmemScOff + w * 768;
            auto fetch = [&](int n, auto tag) {
                constexpr bool V = decltype(tag)::value;
                const int row0 = (V ? (n >> 1) - 1 : (n + 1) >> 1) * 128 + qt * 8;
                if (elect()) {
                    if (V) {
                        mbar_expect_tx(my_bar + 8, 4096);
                        bulk_g2s(my_raw + 8192, p.qv + (h * kS + row0) * kD, 4096, my_bar + 8);
                    } else {
                        mbar_expect_tx(my_bar, 8192);
                        bulk_g2s(my_raw, p.qk + (h * kS + row0) * kD, 4096, my_bar);
                        bulk_g2s(my_raw + 4096, p.k_cos + row0 * kD, 2048, my_bar);
                        bulk_g2s(my_raw + 6144, p.k_sin + row0 * kD, 2048, my_bar);
                    }
                }
            };
            auto fetch_scales = [&](int k) {
                const int n = first + 3 * k;
                const int hr = h * kS + ((n & 1) ? (n + 1) >> 1 : (n >> 1) - 1) * 128 + qt * 8 + (lane & 7);
                const __nv_bfloat16* base = (n & 1) ? ((lane & 8) ? p.k_zeros : p.k_scales) : ((lane & 8) ? p.v_zeros : p.v_scales);
                if (n <= last) asm volatile("cp.async.ca.shared.global [%0], [%1], 4;" ::"r"(my_sc + k * 64 + (lane & 15) * 4), "l"(base + hr * 2) : "memory");
            };
            if (elect()) {
                mbar_init(my_bar, 1); mbar_init(my_bar + 8, 1);
                if (w == 1) for (int i = 0; i < 16; i++) mbar_init(bar_q + 8 * i, 33);
                asm volatile("fence.mbarrier_init.release.cluster;" ::: "memory");
            }
            __syncwarp();
            asm volatile("barrier.cluster.arrive.relaxed.aligned;" ::: "memory");
            fetch_scales(lane >> 4);
            asm volatile("cp.async.commit_group;" ::: "memory");
            if (w == 1) {
#pragma unroll 1
                for (int k = 0; k < 8; k++) {
                    wait_until(t0, p.t_q + h * p.lag_q + k * (p.dt_q - h * p.catch_q) + (k >> 2) * p.gap_q);
#pragma unroll
                    for (int e = 0; e < 2; e++) {
                        const int cw = (k & 4) + (k & 1) * 2 + e, half = (k >> 1) & 1;
                        const int row = qt * 128 + cw * 16 + half * 8;
                        const uint32_t d = sbase + kSmemVOff + (k >> 2) * kVSlotBytes + (cw & 3) * 4096 + half * 2048, bar = bar_q + 16 * cw + 8 * half;
                        const uint32_t dl = d + ((lane * 16) ^ ((lane & 16) << 2));
                        const uint8_t* sl = (const uint8_t*)(p.q + (h * kS + row) * kD + lane * 8);
#pragma unroll
                        for (int i = 0; i < 4; i++)
                            asm volatile("cp.async.cg.shared.global [%0], [%1], 16;" ::"r"(dl + i * 512), "l"(sl + i * 512) : "memory");
                        asm volatile("cp.async.mbarrier.arrive.noinc.shared::cta.b64 [%0];" ::"r"(bar) : "memory");
                        if (elect()) {
                            mbar_expect_tx(bar, 4096);
                            bulk_g2s(d + 16384, p.q_cos + row * kD, 2048, bar);
                            bulk_g2s(d + 32768, p.q_sin + row * kD, 2048, bar);
                        }
                    }
                    if (k == p.k_v1) fetch(4, Tag<true>{});
                }
            } else {
                wait_until(t0, w == 0 ? p.t_v0 : p.t_k2);
                if (w == 0) fetch(2, Tag<true>{}); else fetch(3, Tag<false>{});
            }
            const int r = lane >> 2, c = lane & 3, x = r & 3;
            const uint32_t ia = my_raw + r * 512 + c * 32 + (x >> 1) * 128 + (x & 1) * 16;
            const uint32_t ca = my_raw + 4096 + r * 256 + c * 16 + (x >> 1) * 64 + (x & 1) * 8;
            const uint32_t oa = my_out + r * 128 + c * 4 + (((2 * x) ^ r) << 4);
            const int back = (lane & 16) * 1024 + (lane & 15) * 64 - lane * 16;
            uint8_t* dst = g_scratch + (size_t)(h * kItems + first) * kTileBytes + qt * 1024 + lane * 16;
            uint32_t sa = my_sc + r * 4;
            auto convert = [&](int n, auto tag) {
                constexpr bool V = decltype(tag)::value;
                dequant_slice<V>(ia + (V ? 8192 : 0), ca, oa, lds32(sa), lds32(sa + 32));
                __syncwarp();
                const uint4 v0 = lds128(my_out + lane * 16), v1 = lds128(my_out + 512 + lane * 16);
                const uint4 v2 = lds128(my_out + 1024 + lane * 16), v3 = lds128(my_out + 1536 + lane * 16);
                uint4* d = reinterpret_cast<uint4*>(dst);
                d[0] = v0; d[32] = v1; d[1024] = v2; d[1056] = v3;
                return ld_gpu(dst + back);
            };
            auto publish = [&](int n, uint32_t seen) {
                const uint32_t one = 1u + (__reduce_or_sync(0xffffffffu, seen) & p.zero[0]);
                if (elect()) red_gpu(g_flags + (h * kItems + n) * kFlagStride, one);
                dst += (size_t)kDqWarps * kTileBytes;
                sa += 64;
            };
            auto round0 = [&](auto tag) {
                constexpr bool V = decltype(tag)::value;
                asm volatile("cp.async.wait_group 0;" ::: "memory");
                mbar_wait_idle(my_bar + (V ? 8 : 0), 0);
                __syncwarp();
                const uint32_t seen = convert(first, tag);
                const int due = p.t_next + (first - 2) * p.dt_next;
                const bool soon = __any_sync(0xffffffffu, (int)(clock32() - t0) + 800 >= due);
                if (!soon) publish(first, seen);
                wait_until(t0, due);
                fetch(first + kDqWarps, Tag<!V>{});
                if (soon) publish(first, seen);
            };
            if (first & 1) round0(Tag<false>{}); else round0(Tag<true>{});
#pragma unroll 1
            for (int k = 2; k < 12; k += 2) fetch_scales(k + (lane >> 4));
            asm volatile("cp.async.commit_group;" ::: "memory");
            uint32_t round = 1;
            auto item = [&](int n, auto tag) {
                constexpr bool V = decltype(tag)::value;
                mbar_wait_idle(my_bar + (V ? 8 : 0), round >> 1);
                if (n + kDqWarps <= last) fetch(n + kDqWarps, Tag<!V>{});
                const uint32_t seen = convert(n, tag);
                asm volatile("cp.async.wait_group 0;" ::: "memory");
                publish(n, seen);
            };
#pragma unroll 1
            for (int n = first + kDqWarps; n <= last; n += kDqWarps, round++) {
                if (n & 1) item(n, Tag<false>{}); else item(n, Tag<true>{});
            }
            asm volatile("barrier.cluster.wait.aligned;" ::: "memory");
        }
    } else {
        const int wg = warp >> 2;
        const int g = lane >> 2, c = lane & 3;
        RowsIn kin;
        rows_load<false>(kin, p, h, wg * 128 + qt * 8 + 2 * (warp & 3) + (lane >> 4), lane & 15);
        asm volatile("barrier.cluster.arrive.relaxed.aligned;" ::: "memory");
        asm volatile("setmaxnreg.inc.sync.aligned.u32 224;");
        {
            const uint8_t* at = rows_store<false>(kin, g_scratch + (size_t)(h * kItems + wg) * kTileBytes + qt * 1024,
                                                  2 * (warp & 3) + (lane >> 4), lane & 15);
            const bool never = bar_red_or(4 + wg, 128, (ld_gpu(at) & p.zero[0]) != 0);
            if ((warp & 3) == 0 && elect()) red_gpu(g_flags + (h * kItems + wg) * kFlagStride, never ? 0u : 1u);
        }
        const uint32_t rel_addr = mapa(bar_empty, lane & 1);
        const bool rel = lane < 2;
        asm volatile("barrier.cluster.wait.acquire.aligned;" ::: "memory");
        if (rel) mbar_arrive_cluster(rel_addr + 8 * (3 - wg));

        uint32_t q[32];
        {
            const uint32_t a = sbase + kSmemVOff + wg * kVSlotBytes + (warp & 3) * 4096 + g * 256 + c * 16;
#pragma unroll
            for (int r = 0; r < 2; r++) {
                mbar_wait(bar_q + 16 * warp + 8 * r, 0);
#pragma unroll
                for (int j = 0; j < 2; j++) {
                    const uint32_t bq = a + r * 2048 + ((j * 64) ^ ((g & 1) * 64)), bt = a + r * 2048 + j * 64;
                    const uint4 lo = lds128(bq), hi = lds128(bq + 128);
                    const uint4 cl = lds128(bt + 16384), ch = lds128(bt + 16384 + 128);
                    const uint4 sl = lds128(bt + 32768), sh = lds128(bt + 32768 + 128);
                    uint32_t* ql = q + 8 * j + r;
                    uint32_t* qh = ql + 16;
                    ql[0] = hsub2(hmul2(lo.x, cl.x), hmul2(hi.x, sl.x)); qh[0] = hadd2(hmul2(hi.x, ch.x), hmul2(lo.x, sh.x));
                    ql[2] = hsub2(hmul2(lo.y, cl.y), hmul2(hi.y, sl.y)); qh[2] = hadd2(hmul2(hi.y, ch.y), hmul2(lo.y, sh.y));
                    ql[4] = hsub2(hmul2(lo.z, cl.z), hmul2(hi.z, sl.z)); qh[4] = hadd2(hmul2(hi.z, ch.z), hmul2(lo.z, sh.z));
                    ql[6] = hsub2(hmul2(lo.w, cl.w), hmul2(hi.w, sl.w)); qh[6] = hadd2(hmul2(hi.w, ch.w), hmul2(lo.w, sh.w));
                }
            }
        }

        float s[64], o[kON];
        uint32_t pr[32];
        float ms0, ms1;
        const uint32_t sb4 = (sbase & 0x3FFFF) >> 4;
        const uint64_t dk0 = kDescK | sb4, dv0 = kDescV | (sb4 + (kSmemVOff >> 4));
        const uint32_t id_mine = __shfl_sync(0xffffffffu, 1 + wg, lane), id_other = __shfl_sync(0xffffffffu, 2 - wg, lane);

        {
            float s0[64];
            if (wg == 1) bar_sync(2, 256);
            mbar_wait(bar_full, 0);
            WG_FENCE();
            gemm_qk(s0, q, dk0);
            WG_COMMIT();
            {
                bar_sync(6 + wg, 128);
                const int t = threadIdx.x & 127;
                asm volatile("st.shared.v4.u32 [%0], {%1,%1,%1,%1};" ::"r"(sbase + kSmemVOff + wg * kVSlotBytes + 32768 + (t >> 3) * 1024 + (t & 7) * 144),
                             "r"(0x3F803F80u) : "memory");
                asm volatile("fence.proxy.async.shared::cta;" ::: "memory");
                __syncwarp();
                if (rel) mbar_arrive_cluster(rel_addr + 8 * (2 + wg));
            }
            wg_wait<0>();
            fence_regs(s0);
            bar_arrive(id_other, 256);
            if (rel) mbar_arrive_cluster(rel_addr);
            sched_boundary(p.zero[4]);
            row_max(s0, ms0, ms1);
            ms0 *= kScale; ms1 *= kScale;
            exp_tile<0, kExpSplit0>(s0, ms0, ms1);
            if (wg == 0) exp_tile<kExpSplit0, 16>(s0, ms0, ms1);
            mbar_wait(bar_full + 8, 0);
            bar_sync(id_mine, 256);
            WG_FENCE();
            gemm_qk(s, q, dk0 + (kTileBytes >> 4));
            WG_COMMIT();
            if (wg == 1) exp_tile<kExpSplit0, 16>(s0, ms0, ms1);
            pack_tile(pr, s0);
        }
#pragma unroll
        for (int i = 0; i < kON; i++) o[i] = 0.f;

        uint64_t dk = dk0, dv = dv0;
        auto finish = [&](int j, int ks, int vs, uint32_t vpar, uint32_t z) {
            mbar_wait(bar_full + 16 + 8 * vs, vpar);
            fence_regs(o); fence_regs(pr);
            WG_FENCE();
            gemm_pv(o, pr, dv + vs * (kVSlotBytes >> 4));
            WG_COMMIT();
            bar_arrive(id_other, 256);
            wg_wait<1>();
            fence_regs(s);
            if (rel) mbar_arrive_cluster(rel_addr + 8 * ks);
            exp_tile<0, kExpSplit>(s, ms0, ms1);
            sched_boundary(z);
            wg_wait<0>();
            fence_regs(o); fence_regs(s);
            if (rel) mbar_arrive_cluster(rel_addr + 16 + 8 * vs);
            exp_tile<kExpSplit, 16>(s, ms0, ms1);
            pack_tile(pr, s);
        };
        auto step = [&](int j, int ks, int vs, uint32_t kpar, uint32_t vpar, uint32_t z) {
            mbar_wait(bar_full + 8 * ks, kpar);
            bar_sync(id_mine, 256);
            fence_regs(s);
            WG_FENCE();
            gemm_qk(s, q, dk + ks * (kTileBytes >> 4));
            WG_COMMIT();
            finish(j, ks, vs, vpar, z);
        };
        finish(1, 1, 0, 0, p.zero[2]);
#pragma unroll 1
        for (int i = 1; i < 8; i++) {
            step(2 * i, 0, 1, i, i + 1, p.zero[0]);
            step(2 * i + 1, 1, 0, i, i, p.zero[1]);
            dk += p.zero[0]; dv += p.zero[0];
        }
        asm volatile("barrier.cluster.arrive.relaxed.aligned;" ::: "memory");

        __nv_bfloat16* op = p.out + (h * kS + qt * 128 + warp * 16 + g) * kD + 8 * c;
        bool ok;
        {
            float hi[36], lo[32];
            const float fz = __uint_as_float(p.zero[1]);
#pragma unroll
            for (int i = 0; i < 36; i++) hi[i] = o[32 + i] + fz;
#pragma unroll
            for (int i = 0; i < 32; i++) lo[i] = o[i] + fz;
            mbar_wait(bar_full + 24, 1);
            fence_regs(hi); fence_regs(lo); fence_regs(pr);
            WG_FENCE();
            const uint64_t d = dv0 + (kVSlotBytes >> 4);
#pragma unroll
            for (int kk = 0; kk < 8; kk++) wgmma_pv_hi(hi, pr[4 * kk], pr[4 * kk + 1], pr[4 * kk + 2], pr[4 * kk + 3], d + ((kk * 2048 + 16384) >> 4));
            WG_COMMIT();
#pragma unroll
            for (int kk = 0; kk < 8; kk++) wgmma_pv_lo(lo, pr[4 * kk], pr[4 * kk + 1], pr[4 * kk + 2], pr[4 * kk + 3], d + ((kk * 2048) >> 4));
            WG_COMMIT();
            wg_wait<1>();
            fence_regs(hi);
            const float i0 = rcp(hi[32]), i1 = rcp(hi[34]);
            uint4 u[4], v[4];
            store_half(op + 64, u, hi, 0, i0, i1);
            sched_boundary(p.zero[5]);
            wg_wait<0>();
            fence_regs(lo);
            store_half(op, v, lo, 0, i0, i1);
            sched_boundary(p.zero[6]);
            if (wg == 0) bar_sync(1, 256);
            ok = all_finite(u, v, __shfl_sync(0xffffffffu, 0u, lane)) && hi[32] <= 1.2379400e27f && hi[34] <= 1.2379400e27f;
        }

        if (bar_red_or(3, 256, !ok)) {
            float m0 = -INFINITY, m1 = -INFINITY;
#pragma unroll
            for (int i = 0; i < kON; i++) o[i] = 0.f;
            const uint8_t* src = g_scratch + (size_t)h * kItems * kTileBytes;
#pragma unroll 1
            for (int j = 0; j < 16; j++) {
                if (threadIdx.x == 0) {
                    mbar_expect_tx(bar_fb, 2 * kTileBytes);
                    bulk_g2s(sbase, src + (size_t)(j == 0 ? 0 : 2 * j - 1) * kTileBytes, kTileBytes, bar_fb);
                    bulk_g2s(sbase + kSmemVOff, src + (size_t)(2 * j + 2) * kTileBytes, kTileBytes, bar_fb);
                }
                mbar_wait(bar_fb, j & 1);
                fence_regs(s);
                WG_FENCE();
                gemm_qk(s, q, dk0);
                WG_COMMIT();
                wg_wait<0>();
                fence_regs(s);
                float a0, a1;
                row_max(s, a0, a1);
                a0 = fmaxf(a0, m0); a1 = fmaxf(a1, m1);
                const float r0 = a0 == -INFINITY ? 0.f : a0, r1 = a1 == -INFINITY ? 0.f : a1;
                const float al0 = ex2((m0 - r0) * kScale), al1 = ex2((m1 - r1) * kScale);
                m0 = a0; m1 = a1;
                exp_tile<0, 16>(s, r0 * kScale, r1 * kScale);
                pack_tile(pr, s);
#pragma unroll
                for (int n = 0; n < kON / 4; n++) { o[4 * n] *= al0; o[4 * n + 1] *= al0; o[4 * n + 2] *= al1; o[4 * n + 3] *= al1; }
                fence_regs(o); fence_regs(pr);
                WG_FENCE();
                gemm_pv(o, pr, dv0);
                WG_COMMIT();
                wg_wait<0>();
                fence_regs(o);
                bar_sync(3, 256);
            }
            uint4 v[4];
            store_half(op, v, o, 0, 1.f / o[64], 1.f / o[66]);
            store_half(op + 64, v, o, 32, 1.f / o[64], 1.f / o[66]);
        }
        asm volatile("barrier.cluster.wait.aligned;" ::: "memory");
    }
}

}

extern "C" void kernel_launch(void* const* d_in, const int* in_sizes, int n_in, void* d_out, int out_size) {
    (void)in_sizes; (void)n_in; (void)out_size;
    Params p;
    p.q = (const __nv_bfloat16*)d_in[0];
    p.qk = (const int*)d_in[1];
    p.k_scales = (const __nv_bfloat16*)d_in[2];
    p.k_zeros = (const __nv_bfloat16*)d_in[3];
    p.qv = (const int*)d_in[4];
    p.v_scales = (const __nv_bfloat16*)d_in[5];
    p.v_zeros = (const __nv_bfloat16*)d_in[6];
    p.q_cos = (const __nv_bfloat16*)d_in[7];
    p.q_sin = (const __nv_bfloat16*)d_in[8];
    p.k_cos = (const __nv_bfloat16*)d_in[9];
    p.k_sin = (const __nv_bfloat16*)d_in[10];
    p.out = (__nv_bfloat16*)d_out;
    for (int i = 0; i < 8; i++) p.zero[i] = 0;
    p.t_v0 = 950; p.t_q = 300; p.dt_q = 630; p.t_next = 6200; p.dt_next = 475; p.t_k2 = 2800; p.gap_q = 200; p.k_v1 = 7;
    p.t_poll = 2400; p.stagger = 60; p.lag_q = 140; p.catch_q = 24;
    static int co_resident = -1;
    if (co_resident < 0) {
        cudaFuncSetAttribute(attn_kernel, cudaFuncAttributeMaxDynamicSharedMemorySize, kSmemBytes);
        cudaLaunchConfig_t cfg = {};
        cfg.gridDim = dim3(kH * 16); cfg.blockDim = dim3(384); cfg.dynamicSmemBytes = kSmemBytes;
        cudaLaunchAttribute at;
        at.id = cudaLaunchAttributeClusterDimension;
        at.val.clusterDim.x = 2; at.val.clusterDim.y = 1; at.val.clusterDim.z = 1;
        cfg.attrs = &at; cfg.numAttrs = 1;
        int clusters = 0;
        co_resident = cudaOccupancyMaxActiveClusters(&clusters, attn_kernel, &cfg) == cudaSuccess && clusters >= kH * 8;
        (void)cudaGetLastError();
    }
    if (!co_resident) prefill_kernel<<<kItems * kH * 16, 128>>>(p);
    attn_kernel<<<kH * 16, 384, kSmemBytes>>>(p);
}
```

```cpp
#include <cuda_runtime.h>
#include <cuda_bf16.h>
#include <stdint.h>

namespace {

constexpr int kH = 8, kS = 2048, kD = 128;
constexpr int kItems = 33;
constexpr int kTileBytes = 32768;
constexpr int kVSlotBytes = 49152;
constexpr int kDqWarps = 3;
constexpr int kRawBytes = 12288;
constexpr int kSmemVOff = 2 * kTileBytes;
constexpr int kSmemRawOff = kSmemVOff + 2 * kVSlotBytes;
constexpr int kSmemOutOff = kSmemRawOff + kDqWarps * kRawBytes;
constexpr int kSmemScOff = kSmemOutOff + kDqWarps * 2048;
constexpr int kSmemBarOff = kSmemScOff + kDqWarps * 768;
constexpr int kSmemBytes = kSmemBarOff + 512 + 1024;
constexpr int kFlagStride = 64;
constexpr int kON = 68;
constexpr float kScale = 0.08838834764831845f * 1.4426950408889634f;
constexpr uint32_t kWaitLimit = 1u << 30;
constexpr int kExpSplit = 9;
constexpr int kExpSplit0 = 10;

__device__ __align__(1024) uint8_t g_scratch[(size_t)kH * kItems * kTileBytes];
__device__ __align__(256) unsigned g_flags[kH * kItems * kFlagStride];
__device__ unsigned g_done;

#define TRX TR

struct Params {
    const __nv_bfloat16* q;
    const int* qk;
    const __nv_bfloat16* k_scales;
    const __nv_bfloat16* k_zeros;
    const int* qv;
    const __nv_bfloat16* v_scales;
    const __nv_bfloat16* v_zeros;
    const __nv_bfloat16* q_cos;
    const __nv_bfloat16* q_sin;
    const __nv_bfloat16* k_cos;
    const __nv_bfloat16* k_sin;
    __nv_bfloat16* out;
    uint32_t zero[8];
    int t_v0, t_q, dt_q, t_next, dt_next, t_k2, gap_q, k_v1, t_poll, stagger, lag_q, catch_q, t_tile1, t_tile2;
};

__device__ __forceinline__ uint32_t smem_u32(const void* p) { return (uint32_t)__cvta_generic_to_shared(p); }
__device__ __forceinline__ uint32_t clock32() {
    uint32_t c;
    asm volatile("mov.u32 %0, %%clock;" : "=r"(c));
    return c;
}
__device__ __forceinline__ void wait_until(uint32_t t0, int t) {
    while ((int)(clock32() - t0) < t) {}
    __syncwarp();
}
__device__ __forceinline__ bool elect() {
    uint32_t r;
    asm volatile("{\n.reg .pred p;\nelect.sync _|p, 0xffffffff;\nselp.u32 %0, 1, 0, p;\n}\n" : "=r"(r));
    return r != 0;
}
__device__ __forceinline__ void mbar_init(uint32_t bar, uint32_t count) {
    asm volatile("mbarrier.init.shared::cta.b64 [%0], %1;" ::"r"(bar), "r"(count) : "memory");
}
__device__ __forceinline__ void mbar_expect_tx(uint32_t bar, uint32_t bytes) {
    asm volatile("mbarrier.arrive.expect_tx.shared::cta.b64 _, [%0], %1;" ::"r"(bar), "r"(bytes) : "memory");
}
__device__ __forceinline__ bool mbar_try(uint32_t bar, uint32_t parity) {
    uint32_t ok;
    asm volatile(
        "{\n.reg .pred p;\n"
        "mbarrier.try_wait.parity.shared::cta.b64 p, [%1], %2;\n"
        "selp.u32 %0, 1, 0, p;\n}\n"
        : "=r"(ok)
        : "r"(bar), "r"(parity)
        : "memory");
    return ok != 0;
}
__device__ __forceinline__ void mbar_wait(uint32_t bar, uint32_t parity) {
    if (mbar_try(bar, parity)) return;
    const uint32_t t0 = clock32();
    while (!mbar_try(bar, parity)) {
        if (clock32() - t0 > kWaitLimit) break;
    }
}
__device__ __forceinline__ void mbar_wait_idle(uint32_t bar, uint32_t parity) {
    if (mbar_try(bar, parity)) return;
    const uint32_t t0 = clock32();
    uint32_t ok;
    do {
        asm volatile(
            "{\n.reg .pred p;\n"
            "mbarrier.try_wait.parity.shared::cta.b64 p, [%1], %2, 20000;\n"
            "selp.u32 %0, 1, 0, p;\n}\n"
            : "=r"(ok)
            : "r"(bar), "r"(parity)
            : "memory");
    } while (!ok && clock32() - t0 <= kWaitLimit);
    __syncwarp();
}
__device__ __forceinline__ void mbar_arrive_cluster(uint32_t cluster_addr) {
    asm volatile("mbarrier.arrive.shared::cluster.b64 _, [%0];" ::"r"(cluster_addr) : "memory");
}
__device__ __forceinline__ uint32_t mapa(uint32_t addr, uint32_t rank) {
    uint32_t r;
    asm("mapa.shared::cluster.u32 %0, %1, %2;" : "=r"(r) : "r"(addr), "r"(rank));
    return r;
}
__device__ __forceinline__ void bulk_g2s(uint32_t dst, const void* src, uint32_t bytes, uint32_t bar) {
    asm volatile("cp.async.bulk.shared::cluster.global.mbarrier::complete_tx::bytes [%0], [%1], %2, [%3];" ::"r"(dst),
                 "l"(src), "r"(bytes), "r"(bar)
                 : "memory");
}
__device__ __forceinline__ void bulk_g2s_mc(uint32_t dst, const void* src, uint32_t bytes, uint32_t bar, uint16_t mask) {
    asm volatile(
        "cp.async.bulk.shared::cluster.global.mbarrier::complete_tx::bytes.multicast::cluster [%0], [%1], %2, [%3], %4;" ::"r"(dst),
        "l"(src), "r"(bytes), "r"(bar), "h"(mask)
        : "memory");
}
__device__ __forceinline__ void bar_sync(int id, int n) { asm volatile("bar.sync %0, %1;" ::"r"(id), "r"(n) : "memory"); }
__device__ __forceinline__ void bar_arrive(int id, int n) { asm volatile("bar.arrive %0, %1;" ::"r"(id), "r"(n) : "memory"); }
__device__ __forceinline__ bool bar_red_or(int id, int n, bool v) {
    uint32_t r;
    asm volatile(
        "{\n.reg .pred p, q;\nsetp.ne.u32 q, %3, 0;\n"
        "bar.red.or.pred p, %1, %2, q;\nselp.u32 %0, 1, 0, p;\n}\n"
        : "=r"(r)
        : "r"(id), "r"(n), "r"((uint32_t)v)
        : "memory");
    return r != 0;
}
__device__ __forceinline__ void sched_boundary(uint32_t zero) {
    asm volatile("{\n.reg .pred p;\nsetp.ne.u32 p, %0, 0;\n@p exit;\n}\n" ::"r"(zero) : "memory");
}
__device__ __forceinline__ float ex2(float x) {
    float y;
    asm("ex2.approx.ftz.f32 %0, %1;" : "=f"(y) : "f"(x));
    return y;
}
__device__ __forceinline__ float rcp(float x) {
    float y;
    asm("rcp.approx.ftz.f32 %0, %1;" : "=f"(y) : "f"(x));
    return y;
}
__device__ __forceinline__ uint32_t pack_bf16(float lo, float hi) {
    uint32_t r;
    asm("cvt.rn.bf16x2.f32 %0, %1, %2;" : "=r"(r) : "f"(hi), "f"(lo));
    return r;
}
__device__ __forceinline__ uint32_t hmul2(uint32_t a, uint32_t b) {
    uint32_t r;
    asm("mul.rn.bf16x2 %0, %1, %2;" : "=r"(r) : "r"(a), "r"(b));
    return r;
}
__device__ __forceinline__ uint32_t hadd2(uint32_t a, uint32_t b) {
    uint32_t r;
    asm("add.rn.bf16x2 %0, %1, %2;" : "=r"(r) : "r"(a), "r"(b));
    return r;
}
__device__ __forceinline__ uint32_t hsub2(uint32_t a, uint32_t b) {
    uint32_t r;
    asm("sub.rn.bf16x2 %0, %1, %2;" : "=r"(r) : "r"(a), "r"(b));
    return r;
}
__device__ __forceinline__ uint32_t hfma2(uint32_t a, uint32_t b, uint32_t c) {
    uint32_t r;
    asm("fma.rn.bf16x2 %0, %1, %2, %3;" : "=r"(r) : "r"(a), "r"(b), "r"(c));
    return r;
}
__device__ __forceinline__ uint4 lds128(uint32_t a) {
    uint4 v;
    asm volatile("ld.shared.v4.u32 {%0,%1,%2,%3}, [%4];" : "=r"(v.x), "=r"(v.y), "=r"(v.z), "=r"(v.w) : "r"(a));
    return v;
}
__device__ __forceinline__ uint2 lds64(uint32_t a) {
    uint2 v;
    asm volatile("ld.shared.v2.u32 {%0,%1}, [%2];" : "=r"(v.x), "=r"(v.y) : "r"(a));
    return v;
}
__device__ __forceinline__ uint32_t lds32(uint32_t a) {
    uint32_t v;
    asm volatile("ld.shared.u32 %0, [%1];" : "=r"(v) : "r"(a));
    return v;
}
__device__ __forceinline__ void sts32(uint32_t a, uint32_t v) { asm volatile("st.shared.u32 [%0], %1;" ::"r"(a), "r"(v) : "memory"); }
__device__ __forceinline__ uint4 ldg128(const void* p) {
    uint4 v;
    asm volatile("ld.global.nc.L1::no_allocate.v4.u32 {%0,%1,%2,%3}, [%4];" : "=r"(v.x), "=r"(v.y), "=r"(v.z), "=r"(v.w) : "l"(p) : "memory");
    return v;
}
__device__ __forceinline__ uint2 ldg64(const void* p) {
    uint2 v;
    asm volatile("ld.global.nc.L1::no_allocate.v2.u32 {%0,%1}, [%2];" : "=r"(v.x), "=r"(v.y) : "l"(p) : "memory");
    return v;
}
__device__ __forceinline__ uint32_t ldg32(const void* p) {
    uint32_t v;
    asm volatile("ld.global.nc.L1::no_allocate.u32 %0, [%1];" : "=r"(v) : "l"(p) : "memory");
    return v;
}
__device__ __forceinline__ uint32_t ld_gpu(const void* p) {
    uint32_t v;
    asm volatile("ld.relaxed.gpu.global.u32 %0, [%1];" : "=r"(v) : "l"(p) : "memory");
    return v;
}
__device__ __forceinline__ void red_gpu(unsigned* p, uint32_t v) {
    asm volatile("red.relaxed.gpu.global.add.u32 [%0], %1;" ::"l"(p), "r"(v) : "memory");
}

#define WG_FENCE() asm volatile("wgmma.fence.sync.aligned;" ::: "memory")
#define WG_COMMIT() asm volatile("wgmma.commit_group.sync.aligned;" ::: "memory")
template <int N>
__device__ __forceinline__ void wg_wait() {
    asm volatile("wgmma.wait_group.sync.aligned %0;" ::"n"(N) : "memory");
}
template <int ACC>
__device__ __forceinline__ void wgmma_qk(float (&d)[64], uint32_t a0, uint32_t a1, uint32_t a2, uint32_t a3, uint64_t db) {
    asm volatile(
        "{\n.reg .pred p;\nsetp.ne.b32 p, %69, 0;\n"
        "wgmma.mma_async.sync.aligned.m64n128k16.f32.bf16.bf16 "
        "{%0,%1,%2,%3,%4,%5,%6,%7,%8,%9,%10,%11,%12,%13,%14,%15,%16,%17,%18,%19,%20,%21,%22,%23,"
        "%24,%25,%26,%27,%28,%29,%30,%31,%32,%33,%34,%35,%36,%37,%38,%39,%40,%41,%42,%43,%44,%45,%46,%47,"
        "%48,%49,%50,%51,%52,%53,%54,%55,%56,%57,%58,%59,%60,%61,%62,%63}, {%64,%65,%66,%67}, %68, p, 1, 1, 0;\n}\n"
        : "+f"(d[0]), "+f"(d[1]), "+f"(d[2]), "+f"(d[3]), "+f"(d[4]), "+f"(d[5]), "+f"(d[6]), "+f"(d[7]),
          "+f"(d[8]), "+f"(d[9]), "+f"(d[10]), "+f"(d[11]), "+f"(d[12]), "+f"(d[13]), "+f"(d[14]), "+f"(d[15]),
          "+f"(d[16]), "+f"(d[17]), "+f"(d[18]), "+f"(d[19]), "+f"(d[20]), "+f"(d[21]), "+f"(d[22]), "+f"(d[23]),
          "+f"(d[24]), "+f"(d[25]), "+f"(d[26]), "+f"(d[27]), "+f"(d[28]), "+f"(d[29]), "+f"(d[30]), "+f"(d[31]),
          "+f"(d[32]), "+f"(d[33]), "+f"(d[34]), "+f"(d[35]), "+f"(d[36]), "+f"(d[37]), "+f"(d[38]), "+f"(d[39]),
          "+f"(d[40]), "+f"(d[41]), "+f"(d[42]), "+f"(d[43]), "+f"(d[44]), "+f"(d[45]), "+f"(d[46]), "+f"(d[47]),
          "+f"(d[48]), "+f"(d[49]), "+f"(d[50]), "+f"(d[51]), "+f"(d[52]), "+f"(d[53]), "+f"(d[54]), "+f"(d[55]),
          "+f"(d[56]), "+f"(d[57]), "+f"(d[58]), "+f"(d[59]), "+f"(d[60]), "+f"(d[61]), "+f"(d[62]), "+f"(d[63])
        : "r"(a0), "r"(a1), "r"(a2), "r"(a3), "l"(db), "n"(ACC));
}
__device__ __forceinline__ void wgmma_pv(float (&d)[kON], uint32_t a0, uint32_t a1, uint32_t a2, uint32_t a3, uint64_t db) {
    asm volatile(
        "wgmma.mma_async.sync.aligned.m64n136k16.f32.bf16.bf16 "
        "{%0,%1,%2,%3,%4,%5,%6,%7,%8,%9,%10,%11,%12,%13,%14,%15,%16,%17,%18,%19,%20,%21,%22,%23,"
        "%24,%25,%26,%27,%28,%29,%30,%31,%32,%33,%34,%35,%36,%37,%38,%39,%40,%41,%42,%43,%44,%45,%46,%47,"
        "%48,%49,%50,%51,%52,%53,%54,%55,%56,%57,%58,%59,%60,%61,%62,%63,%64,%65,%66,%67}, {%68,%69,%70,%71}, %72, 1, 1, 1, 1;\n"
        : "+f"(d[0]), "+f"(d[1]), "+f"(d[2]), "+f"(d[3]), "+f"(d[4]), "+f"(d[5]), "+f"(d[6]), "+f"(d[7]),
          "+f"(d[8]), "+f"(d[9]), "+f"(d[10]), "+f"(d[11]), "+f"(d[12]), "+f"(d[13]), "+f"(d[14]), "+f"(d[15]),
          "+f"(d[16]), "+f"(d[17]), "+f"(d[18]), "+f"(d[19]), "+f"(d[20]), "+f"(d[21]), "+f"(d[22]), "+f"(d[23]),
          "+f"(d[24]), "+f"(d[25]), "+f"(d[26]), "+f"(d[27]), "+f"(d[28]), "+f"(d[29]), "+f"(d[30]), "+f"(d[31]),
          "+f"(d[32]), "+f"(d[33]), "+f"(d[34]), "+f"(d[35]), "+f"(d[36]), "+f"(d[37]), "+f"(d[38]), "+f"(d[39]),
          "+f"(d[40]), "+f"(d[41]), "+f"(d[42]), "+f"(d[43]), "+f"(d[44]), "+f"(d[45]), "+f"(d[46]), "+f"(d[47]),
          "+f"(d[48]), "+f"(d[49]), "+f"(d[50]), "+f"(d[51]), "+f"(d[52]), "+f"(d[53]), "+f"(d[54]), "+f"(d[55]),
          "+f"(d[56]), "+f"(d[57]), "+f"(d[58]), "+f"(d[59]), "+f"(d[60]), "+f"(d[61]), "+f"(d[62]), "+f"(d[63]),
          "+f"(d[64]), "+f"(d[65]), "+f"(d[66]), "+f"(d[67])
        : "r"(a0), "r"(a1), "r"(a2), "r"(a3), "l"(db));
}
__device__ __forceinline__ void wgmma_pv_hi(float (&d)[36], uint32_t a0, uint32_t a1, uint32_t a2, uint32_t a3, uint64_t db) {
    asm volatile(
        "wgmma.mma_async.sync.aligned.m64n72k16.f32.bf16.bf16 "
        "{%0,%1,%2,%3,%4,%5,%6,%7,%8,%9,%10,%11,%12,%13,%14,%15,%16,%17,%18,%19,%20,%21,%22,%23,"
        "%24,%25,%26,%27,%28,%29,%30,%31,%32,%33,%34,%35}, {%36,%37,%38,%39}, %40, 1, 1, 1, 1;\n"
        : "+f"(d[0]), "+f"(d[1]), "+f"(d[2]), "+f"(d[3]), "+f"(d[4]), "+f"(d[5]), "+f"(d[6]), "+f"(d[7]),
          "+f"(d[8]), "+f"(d[9]), "+f"(d[10]), "+f"(d[11]), "+f"(d[12]), "+f"(d[13]), "+f"(d[14]), "+f"(d[15]),
          "+f"(d[16]), "+f"(d[17]), "+f"(d[18]), "+f"(d[19]), "+f"(d[20]), "+f"(d[21]), "+f"(d[22]), "+f"(d[23]),
          "+f"(d[24]), "+f"(d[25]), "+f"(d[26]), "+f"(d[27]), "+f"(d[28]), "+f"(d[29]), "+f"(d[30]), "+f"(d[31]),
          "+f"(d[32]), "+f"(d[33]), "+f"(d[34]), "+f"(d[35])
        : "r"(a0), "r"(a1), "r"(a2), "r"(a3), "l"(db));
}
__device__ __forceinline__ void wgmma_pv_lo(float (&d)[32], uint32_t a0, uint32_t a1, uint32_t a2, uint32_t a3, uint64_t db) {
    asm volatile(
        "wgmma.mma_async.sync.aligned.m64n64k16.f32.bf16.bf16 "
        "{%0,%1,%2,%3,%4,%5,%6,%7,%8,%9,%10,%11,%12,%13,%14,%15,%16,%17,%18,%19,%20,%21,%22,%23,"
        "%24,%25,%26,%27,%28,%29,%30,%31}, {%32,%33,%34,%35}, %36, 1, 1, 1, 1;\n"
        : "+f"(d[0]), "+f"(d[1]), "+f"(d[2]), "+f"(d[3]), "+f"(d[4]), "+f"(d[5]), "+f"(d[6]), "+f"(d[7]),
          "+f"(d[8]), "+f"(d[9]), "+f"(d[10]), "+f"(d[11]), "+f"(d[12]), "+f"(d[13]), "+f"(d[14]), "+f"(d[15]),
          "+f"(d[16]), "+f"(d[17]), "+f"(d[18]), "+f"(d[19]), "+f"(d[20]), "+f"(d[21]), "+f"(d[22]), "+f"(d[23]),
          "+f"(d[24]), "+f"(d[25]), "+f"(d[26]), "+f"(d[27]), "+f"(d[28]), "+f"(d[29]), "+f"(d[30]), "+f"(d[31])
        : "r"(a0), "r"(a1), "r"(a2), "r"(a3), "l"(db));
}
template <int N>
__device__ __forceinline__ void fence_regs(float (&d)[N]) {
#pragma unroll
    for (int i = 0; i < N; i++) asm volatile("" : "+f"(d[i])::"memory");
}
__device__ __forceinline__ void fence_regs(uint32_t (&d)[32]) {
#pragma unroll
    for (int i = 0; i < 32; i++) asm volatile("" : "+r"(d[i])::"memory");
}
constexpr uint64_t kDescK = (uint64_t(1) << 62) | (uint64_t(1024 >> 4) << 32) | (uint64_t(1) << 16);
constexpr uint64_t kDescV = (uint64_t(1) << 62) | (uint64_t(1024 >> 4) << 32) | (uint64_t(16384 >> 4) << 16);

__device__ __forceinline__ void gemm_qk(float (&s)[64], const uint32_t (&q)[32], uint64_t d) {
    wgmma_qk<0>(s, q[0], q[1], q[2], q[3], d);
#pragma unroll
    for (int kk = 1; kk < 8; kk++)
        wgmma_qk<1>(s, q[4 * kk], q[4 * kk + 1], q[4 * kk + 2], q[4 * kk + 3], d + (((kk >> 2) * 16384 + (kk & 3) * 32) >> 4));
}
__device__ __forceinline__ void gemm_pv(float (&o)[kON], const uint32_t (&p)[32], uint64_t d) {
#pragma unroll
    for (int kk = 0; kk < 8; kk++) wgmma_pv(o, p[4 * kk], p[4 * kk + 1], p[4 * kk + 2], p[4 * kk + 3], d + ((kk * 2048) >> 4));
}

__device__ __forceinline__ void dequant4(uint32_t (&v)[4], uint32_t sc, uint32_t zp) {
    const uint32_t s0 = __byte_perm(sc, 0, 0x1010), s1 = __byte_perm(sc, 0, 0x3232);
    const uint32_t z0 = __byte_perm(zp, 0, 0x1010), z1 = __byte_perm(zp, 0, 0x3232);
    v[0] = hmul2(hsub2(v[0], z0), s0); v[1] = hmul2(hsub2(v[1], z0), s0);
    v[2] = hmul2(hsub2(v[2], z1), s1); v[3] = hmul2(hsub2(v[3], z1), s1);
}
__device__ __forceinline__ void to_bf16(uint32_t (&v)[4], const uint4& lo, const uint4& hi) {
    v[0] = pack_bf16((float)(int)lo.x, (float)(int)lo.y); v[1] = pack_bf16((float)(int)lo.z, (float)(int)lo.w);
    v[2] = pack_bf16((float)(int)hi.x, (float)(int)hi.y); v[3] = pack_bf16((float)(int)hi.z, (float)(int)hi.w);
}
__device__ __forceinline__ void rope4(uint32_t (&v)[4], const uint2& cl, const uint2& ch, const uint2& sl, const uint2& sh) {
    const uint32_t r0 = hsub2(hmul2(v[0], cl.x), hmul2(v[2], sl.x)), r1 = hsub2(hmul2(v[1], cl.y), hmul2(v[3], sl.y));
    const uint32_t r2 = hadd2(hmul2(v[2], ch.x), hmul2(v[0], sh.x)), r3 = hadd2(hmul2(v[3], ch.y), hmul2(v[1], sh.y));
    v[0] = r0; v[1] = r1; v[2] = r2; v[3] = r3;
}

template <bool IS_V>
__device__ __forceinline__ void dequant_slice(uint32_t ia, uint32_t ca, uint32_t oa, uint32_t sc, uint32_t zp) {
    uint4 lo = lds128(ia), hi = lds128(ia + 256);
#pragma unroll
    for (int it = 0; it < 4; it++) {
        uint2 cl, ch, sl, sh;
        if (!IS_V) {
            const uint32_t a = ca ^ ((it >> 1) * 64 + (it & 1) * 8);
            cl = lds64(a); sl = lds64(a + 2048); ch = lds64(a + 128); sh = lds64(a + 2048 + 128);
        }
        uint32_t v[4];
        to_bf16(v, lo, hi);
        if (it < 3) {
            const uint32_t a = ia ^ (((it + 1) >> 1) * 128 + ((it + 1) & 1) * 16);
            lo = lds128(a); hi = lds128(a + 256);
        }
        dequant4(v, sc, zp);
        if (!IS_V) rope4(v, cl, ch, sl, sh);
        const uint32_t o0 = oa ^ (it << 5), o1 = oa ^ ((it << 5) | 16);
        sts32(o0, v[0]); sts32(o1, v[1]); sts32(o0 + 1024, v[2]); sts32(o1 + 1024, v[3]);
    }
}

struct RowsIn { uint4 lo, hi; uint2 cl, ch, sl, sh; uint32_t sc, zp; };
template <bool IS_V>
__device__ __forceinline__ void rows_load(RowsIn& x, const Params& p, int h, int row, int mp) {
    const int hr = h * kS + row;
    const int* ints = (IS_V ? p.qv : p.qk) + hr * kD + 4 * mp;
    x.lo = ldg128(ints); x.hi = ldg128(ints + 64);
    if (!IS_V) {
        x.cl = ldg64(p.k_cos + row * kD + 4 * mp); x.ch = ldg64(p.k_cos + row * kD + 64 + 4 * mp);
        x.sl = ldg64(p.k_sin + row * kD + 4 * mp); x.sh = ldg64(p.k_sin + row * kD + 64 + 4 * mp);
    }
    x.sc = ldg32((IS_V ? p.v_scales : p.k_scales) + hr * 2); x.zp = ldg32((IS_V ? p.v_zeros : p.k_zeros) + hr * 2);
}
template <bool IS_V>
__device__ __forceinline__ uint8_t* rows_store(const RowsIn& a, uint8_t* slice, int r, int mp) {
    const int j = mp >> 3, c = (mp >> 1) & 3, b = mp & 1;
    uint32_t v[4];
    to_bf16(v, a.lo, a.hi);
    dequant4(v, a.sc, a.zp);
    if (!IS_V) rope4(v, a.cl, a.ch, a.sl, a.sh);
    const bool c0 = c & 1, c1 = c & 2;
    uint32_t x = __shfl_xor_sync(0xffffffffu, c0 ? v[0] : v[1], 2), y = __shfl_xor_sync(0xffffffffu, c0 ? v[2] : v[3], 2);
    const uint32_t a0 = c0 ? x : v[0], a1 = c0 ? v[1] : x, a2 = c0 ? y : v[2], a3 = c0 ? v[3] : y;
    x = __shfl_xor_sync(0xffffffffu, c1 ? a0 : a2, 4); y = __shfl_xor_sync(0xffffffffu, c1 ? a1 : a3, 4);
    uint8_t* dst = slice + (c >> 1) * 16384 + r * 128 + (((4 * j + 2 * b + (c & 1)) ^ r) << 4);
    *reinterpret_cast<uint4*>(dst) = make_uint4(c1 ? x : a0, c1 ? y : a1, c1 ? a2 : x, c1 ? a3 : y);
    return dst;
}

__global__ void __launch_bounds__(128) prefill_kernel(const __grid_constant__ Params p) {
    const int slice = blockIdx.x & 15, h = (blockIdx.x >> 4) & 7, n = blockIdx.x >> 7;
    if (n == kItems - 2) return;
    const int r = threadIdx.x >> 4, mp = threadIdx.x & 15;
    const bool is_v = n != 0 && !(n & 1);
    const int row = (is_v ? (n >> 1) - 1 : (n + 1) >> 1) * 128 + slice * 8 + r;
    uint8_t* dst = g_scratch + (size_t)(h * kItems + n) * kTileBytes + slice * 1024;
    RowsIn x;
    if (is_v) { rows_load<true>(x, p, h, row, mp); rows_store<true>(x, dst, r, mp); }
    else { rows_load<false>(x, p, h, row, mp); rows_store<false>(x, dst, r, mp); }
    if (threadIdx.x == 0 && slice == 0) g_flags[(h * kItems + n) * kFlagStride] = 16;
}

template <int N0, int N1>
__device__ __forceinline__ void exp_tile(float (&s)[64], float ms0, float ms1) {
    if (N0 == 0) {
#pragma unroll
        for (int i = 0; i < 64; i++) s[i] = fmaf(s[i], kScale, (i & 2) ? -ms1 : -ms0);
    }
#pragma unroll
    for (int i = 4 * N0; i < 4 * N1; i++) s[i] = ex2(s[i]);
}
__device__ __forceinline__ void row_max(const float (&s)[64], float& m0, float& m1) {
    float a0 = fmaxf(s[0], s[1]), a1 = fmaxf(s[2], s[3]), b0 = fmaxf(s[4], s[5]), b1 = fmaxf(s[6], s[7]);
#pragma unroll
    for (int n = 2; n < 16; n += 2) {
        a0 = fmaxf(a0, fmaxf(s[4 * n], s[4 * n + 1])); a1 = fmaxf(a1, fmaxf(s[4 * n + 2], s[4 * n + 3]));
        b0 = fmaxf(b0, fmaxf(s[4 * n + 4], s[4 * n + 5])); b1 = fmaxf(b1, fmaxf(s[4 * n + 6], s[4 * n + 7]));
    }
    m0 = fmaxf(a0, b0); m1 = fmaxf(a1, b1);
    m0 = fmaxf(m0, __shfl_xor_sync(0xffffffffu, m0, 1)); m1 = fmaxf(m1, __shfl_xor_sync(0xffffffffu, m1, 1));
    m0 = fmaxf(m0, __shfl_xor_sync(0xffffffffu, m0, 2)); m1 = fmaxf(m1, __shfl_xor_sync(0xffffffffu, m1, 2));
}
__device__ __forceinline__ void pack_tile(uint32_t (&pr)[32], const float (&s)[64]) {
#pragma unroll
    for (int i = 0; i < 32; i++) pr[i] = pack_bf16(s[2 * i], s[2 * i + 1]);
}
template <int N>
__device__ __forceinline__ void store_half(__nv_bfloat16* op, uint4 (&v)[4], const float (&o)[N], int b, float i0, float i1) {
#pragma unroll
    for (int j = 0; j < 2; j++) {
        uint4 &v0 = v[2 * j], &v1 = v[2 * j + 1];
        const float* x = o + b + 16 * j;
        v0.x = pack_bf16(x[0] * i0, x[1] * i0);  v0.y = pack_bf16(x[4] * i0, x[5] * i0);
        v0.z = pack_bf16(x[8] * i0, x[9] * i0);  v0.w = pack_bf16(x[12] * i0, x[13] * i0);
        *reinterpret_cast<uint4*>(op + 32 * j) = v0;
        v1.x = pack_bf16(x[2] * i1, x[3] * i1);  v1.y = pack_bf16(x[6] * i1, x[7] * i1);
        v1.z = pack_bf16(x[10] * i1, x[11] * i1); v1.w = pack_bf16(x[14] * i1, x[15] * i1);
        *reinterpret_cast<uint4*>(op + 8 * kD + 32 * j) = v1;
    }
}
__device__ __forceinline__ bool all_finite(const uint4 (&u)[4], const uint4 (&v)[4], uint32_t zero) {
    uint32_t a[4] = {0, 0, 0, 0};
#pragma unroll
    for (int j = 0; j < 4; j++) {
        a[0] = hfma2(u[j].x, zero, hfma2(v[j].x, zero, a[0])); a[1] = hfma2(u[j].y, zero, hfma2(v[j].y, zero, a[1]));
        a[2] = hfma2(u[j].z, zero, hfma2(v[j].z, zero, a[2])); a[3] = hfma2(u[j].w, zero, hfma2(v[j].w, zero, a[3]));
    }
    return ((a[0] | a[1] | a[2] | a[3]) & 0x7fff7fffu) == 0;
}

template <bool B> struct Tag { static constexpr bool value = B; };

__global__ void __cluster_dims__(2, 1, 1) __launch_bounds__(384, 1) attn_kernel(const __grid_constant__ Params p) {
    extern __shared__ uint8_t smem_raw[];
    const uint32_t sbase = (smem_u32(smem_raw) + 1023) & ~1023u;
    const uint32_t bar_full = sbase + kSmemBarOff;
    const uint32_t bar_empty = bar_full + 32;
    const uint32_t bar_raw = bar_empty + 32;
    const uint32_t bar_q = bar_raw + 16 * kDqWarps;
    const uint32_t bar_fb = bar_q + 128;

    const int h = blockIdx.x >> 4, qt = blockIdx.x & 15;
    const int warp = __shfl_sync(0xffffffffu, threadIdx.x >> 5, 0), lane = threadIdx.x & 31;

    if (warp >= 8) {
        asm volatile("setmaxnreg.dec.sync.aligned.u32 56;");
        if (warp == 8) {
            const uint32_t t0 = clock32();
            const unsigned* fp = g_flags + (h * kItems + lane) * kFlagStride;
            uint32_t early = 0;
            if (lane < 8) early = ld_gpu(fp);
            if (elect()) {
                for (int i = 0; i < 4; i++) {
                    mbar_init(bar_full + 8 * i, 1);
                    mbar_init(bar_empty + 8 * i, 16);
                }
                mbar_init(bar_fb, 1);
                asm volatile("fence.mbarrier_init.release.cluster;" ::: "memory");
            }
            __syncwarp();
            asm volatile("barrier.cluster.arrive.relaxed.aligned;" ::: "memory");
            asm volatile("barrier.cluster.wait.acquire.aligned;" ::: "memory");
            const uint32_t rank = blockIdx.x & 1;
            const uint8_t* src = g_scratch + (size_t)h * kItems * kTileBytes + rank * (kTileBytes / 2);
            uint32_t ready = __ballot_sync(0xffffffffu, early >= 16);
            asm volatile("fence.acquire.gpu;" ::: "memory");
            uint32_t parity = 3;
            wait_until(t0, p.t_poll);
#pragma unroll 1
            for (int n = 0; n < kItems; n++, ready >>= 1, src += kTileBytes, fp += kFlagStride) {
                if (n == kItems - 2) continue;
                const bool mine = lane < 2 && n + lane < kItems;
                if (!(ready & 1)) {
                    const uint32_t t1 = clock32();
                    do {
                        ready = __ballot_sync(0xffffffffu, mine && ld_gpu(fp) >= 16);
                    } while (!(ready & 1) && !__any_sync(0xffffffffu, clock32() - t1 > kWaitLimit));
                    asm volatile("fence.acquire.gpu;" ::: "memory");
                }
                const bool is_v = n != 0 && !(n & 1);
                const int odd = (((n + 1) >> 1) & 1) ^ (is_v ? 1 : 0);
                const int slot = (is_v ? 2 : 0) + odd;
                const bool peek = !(ready & 2);
                uint32_t ahead = 0;
                if (peek && mine) ahead = ld_gpu(fp);
                if (n == 1) wait_until(t0, p.t_tile1);
                if (n == 2) wait_until(t0, p.t_tile2);
                mbar_wait_idle(bar_empty + 8 * slot, (parity >> slot) & 1);
                if (elect()) {
                    mbar_expect_tx(bar_full + 8 * slot, kTileBytes);
                    const uint32_t dst = sbase + (is_v ? kSmemVOff + odd * kVSlotBytes : odd * kTileBytes);
                    bulk_g2s_mc(dst + rank * (kTileBytes / 2), src, kTileBytes / 2, bar_full + 8 * slot, (uint16_t)3);
                }
                parity ^= 1u << slot;
                if (peek) {
                    ready = __ballot_sync(0xffffffffu, ahead >= 16);
                    asm volatile("fence.acquire.gpu;" ::: "memory");
                }
            }
            uint32_t ticket = 0;
            if (lane == 0) ticket = atomicAdd(&g_done, 1u);
            if (__shfl_sync(0xffffffffu, ticket, 0) == gridDim.x - 1) {
                for (int i = lane; i < kH * kItems; i += 32) g_flags[i * kFlagStride] = 0;
                if (lane == 0) g_done = 0;
            }
        } else {
            const int w = warp - 9;
            const uint32_t t0 = clock32() + p.stagger * h;
            const int first = w == 0 ? 2 : 5 - w;
            const int last = first == 4 ? 28 : kItems - 1;
            const uint32_t my_bar = bar_raw + 16 * w;
            const uint32_t my_raw = sbase + kSmemRawOff + w * kRawBytes;
            const uint32_t my_out = sbase + kSmemOutOff + w * 2048;
            const uint32_t my_sc = sbase + kSmemScOff + w * 768;
            auto fetch = [&](int n, auto tag) {
                constexpr bool V = decltype(tag)::value;
                const int row0 = (V ? (n >> 1) - 1 : (n + 1) >> 1) * 128 + qt * 8;
                if (elect()) {
                    if (V) {
                        mbar_expect_tx(my_bar + 8, 4096);
                        bulk_g2s(my_raw + 8192, p.qv + (h * kS + row0) * kD, 4096, my_bar + 8);
                    } else {
                        mbar_expect_tx(my_bar, 8192);
                        bulk_g2s(my_raw, p.qk + (h * kS + row0) * kD, 4096, my_bar);
                        bulk_g2s(my_raw + 4096, p.k_cos + row0 * kD, 2048, my_bar);
                        bulk_g2s(my_raw + 6144, p.k_sin + row0 * kD, 2048, my_bar);
                    }
                }
            };
            auto fetch_scales = [&](int k) {
                const int n = first + 3 * k;
                const int hr = h * kS + ((n & 1) ? (n + 1) >> 1 : (n >> 1) - 1) * 128 + qt * 8 + (lane & 7);
                const __nv_bfloat16* base = (n & 1) ? ((lane & 8) ? p.k_zeros : p.k_scales) : ((lane & 8) ? p.v_zeros : p.v_scales);
                if (n <= last) asm volatile("cp.async.ca.shared.global [%0], [%1], 4;" ::"r"(my_sc + k * 64 + (lane & 15) * 4), "l"(base + hr * 2) : "memory");
            };
            if (elect()) {
                mbar_init(my_bar, 1); mbar_init(my_bar + 8, 1);
                if (w == 1) for (int i = 0; i < 16; i++) mbar_init(bar_q + 8 * i, 33);
                asm volatile("fence.mbarrier_init.release.cluster;" ::: "memory");
            }
            __syncwarp();
            asm volatile("barrier.cluster.arrive.relaxed.aligned;" ::: "memory");
            fetch_scales(lane >> 4);
            asm volatile("cp.async.commit_group;" ::: "memory");
            if (w == 1) {
#pragma unroll 1
                for (int k = 0; k < 8; k++) {
                    wait_until(t0, p.t_q + h * p.lag_q + k * (p.dt_q - h * p.catch_q) + (k >> 2) * p.gap_q);
#pragma unroll
                    for (int e = 0; e < 2; e++) {
                        const int cw = (k & 4) + (k & 1) * 2 + e, half = (k >> 1) & 1;
                        const int row = qt * 128 + cw * 16 + half * 8;
                        const uint32_t d = sbase + kSmemVOff + (k >> 2) * kVSlotBytes + (cw & 3) * 4096 + half * 2048, bar = bar_q + 16 * cw + 8 * half;
                        const uint32_t dl = d + ((lane * 16) ^ ((lane & 16) << 2));
                        const uint8_t* sl = (const uint8_t*)(p.q + (h * kS + row) * kD + lane * 8);
#pragma unroll
                        for (int i = 0; i < 4; i++)
                            asm volatile("cp.async.cg.shared.global [%0], [%1], 16;" ::"r"(dl + i * 512), "l"(sl + i * 512) : "memory");
                        asm volatile("cp.async.mbarrier.arrive.noinc.shared::cta.b64 [%0];" ::"r"(bar) : "memory");
                        if (elect()) {
                            mbar_expect_tx(bar, 4096);
                            bulk_g2s(d + 16384, p.q_cos + row * kD, 2048, bar);
                            bulk_g2s(d + 32768, p.q_sin + row * kD, 2048, bar);
                        }
                    }
                    if (k == p.k_v1) fetch(4, Tag<true>{});
                }
            } else {
                wait_until(t0, w == 0 ? p.t_v0 : p.t_k2);
                if (w == 0) fetch(2, Tag<true>{}); else fetch(3, Tag<false>{});
            }
            const int r = lane >> 2, c = lane & 3, x = r & 3;
            const uint32_t ia = my_raw + r * 512 + c * 32 + (x >> 1) * 128 + (x & 1) * 16;
            const uint32_t ca = my_raw + 4096 + r * 256 + c * 16 + (x >> 1) * 64 + (x & 1) * 8;
            const uint32_t oa = my_out + r * 128 + c * 4 + (((2 * x) ^ r) << 4);
            const int back = (lane & 16) * 1024 + (lane & 15) * 64 - lane * 16;
            uint8_t* dst = g_scratch + (size_t)(h * kItems + first) * kTileBytes + qt * 1024 + lane * 16;
            uint32_t sa = my_sc + r * 4;
            auto convert = [&](int n, auto tag) {
                constexpr bool V = decltype(tag)::value;
                dequant_slice<V>(ia + (V ? 8192 : 0), ca, oa, lds32(sa), lds32(sa + 32));
                __syncwarp();
                const uint4 v0 = lds128(my_out + lane * 16), v1 = lds128(my_out + 512 + lane * 16);
                const uint4 v2 = lds128(my_out + 1024 + lane * 16), v3 = lds128(my_out + 1536 + lane * 16);
                uint4* d = reinterpret_cast<uint4*>(dst);
                d[0] = v0; d[32] = v1; d[1024] = v2; d[1056] = v3;
                return ld_gpu(dst + back);
            };
            auto publish = [&](int n, uint32_t seen) {
                const uint32_t one = 1u + (__reduce_or_sync(0xffffffffu, seen) & p.zero[0]);
                if (elect()) red_gpu(g_flags + (h * kItems + n) * kFlagStride, one);
                dst += (size_t)kDqWarps * kTileBytes;
                sa += 64;
            };
            auto round0 = [&](auto tag) {
                constexpr bool V = decltype(tag)::value;
                asm volatile("cp.async.wait_group 0;" ::: "memory");
                mbar_wait_idle(my_bar + (V ? 8 : 0), 0);
                __syncwarp();
                const uint32_t seen = convert(first, tag);
                const int due = p.t_next + (first - 2) * p.dt_next;
                const bool soon = __any_sync(0xffffffffu, (int)(clock32() - t0) + 800 >= due);
                if (!soon) publish(first, seen);
                wait_until(t0, due);
                fetch(first + kDqWarps, Tag<!V>{});
                if (soon) publish(first, seen);
            };
            if (first & 1) round0(Tag<false>{}); else round0(Tag<true>{});
#pragma unroll 1
            for (int k = 2; k < 12; k += 2) fetch_scales(k + (lane >> 4));
            asm volatile("cp.async.commit_group;" ::: "memory");
            uint32_t round = 1;
            auto item = [&](int n, auto tag) {
                constexpr bool V = decltype(tag)::value;
                mbar_wait_idle(my_bar + (V ? 8 : 0), round >> 1);
                if (n + kDqWarps <= last) fetch(n + kDqWarps, Tag<!V>{});
                const uint32_t seen = convert(n, tag);
                asm volatile("cp.async.wait_group 0;" ::: "memory");
                publish(n, seen);
            };
#pragma unroll 1
            for (int n = first + kDqWarps; n <= last; n += kDqWarps, round++) {
                if (n & 1) item(n, Tag<false>{}); else item(n, Tag<true>{});
            }
            asm volatile("barrier.cluster.wait.aligned;" ::: "memory");
        }
    } else {
        const int wg = warp >> 2;
        const int g = lane >> 2, c = lane & 3;
        RowsIn kin;
        rows_load<false>(kin, p, h, wg * 128 + qt * 8 + 2 * (warp & 3) + (lane >> 4), lane & 15);
        asm volatile("barrier.cluster.arrive.relaxed.aligned;" ::: "memory");
        asm volatile("setmaxnreg.inc.sync.aligned.u32 224;");
        {
            const uint8_t* at = rows_store<false>(kin, g_scratch + (size_t)(h * kItems + wg) * kTileBytes + qt * 1024,
                                                  2 * (warp & 3) + (lane >> 4), lane & 15);
            const bool never = bar_red_or(4 + wg, 128, (ld_gpu(at) & p.zero[0]) != 0);
            if ((warp & 3) == 0 && elect()) red_gpu(g_flags + (h * kItems + wg) * kFlagStride, never ? 0u : 1u);
        }
        const uint32_t rel_addr = mapa(bar_empty, lane & 1);
        const bool rel = lane < 2;
        asm volatile("barrier.cluster.wait.acquire.aligned;" ::: "memory");
        if (rel) mbar_arrive_cluster(rel_addr + 8 * (3 - wg));

        uint32_t q[32];
        {
            const uint32_t a = sbase + kSmemVOff + wg * kVSlotBytes + (warp & 3) * 4096 + g * 256 + c * 16;
#pragma unroll
            for (int r = 0; r < 2; r++) {
                mbar_wait(bar_q + 16 * warp + 8 * r, 0);
#pragma unroll
                for (int j = 0; j < 2; j++) {
                    const uint32_t bq = a + r * 2048 + ((j * 64) ^ ((g & 1) * 64)), bt = a + r * 2048 + j * 64;
                    const uint4 lo = lds128(bq), hi = lds128(bq + 128);
                    const uint4 cl = lds128(bt + 16384), ch = lds128(bt + 16384 + 128);
                    const uint4 sl = lds128(bt + 32768), sh = lds128(bt + 32768 + 128);
                    uint32_t* ql = q + 8 * j + r;
                    uint32_t* qh = ql + 16;
                    ql[0] = hsub2(hmul2(lo.x, cl.x), hmul2(hi.x, sl.x)); qh[0] = hadd2(hmul2(hi.x, ch.x), hmul2(lo.x, sh.x));
                    ql[2] = hsub2(hmul2(lo.y, cl.y), hmul2(hi.y, sl.y)); qh[2] = hadd2(hmul2(hi.y, ch.y), hmul2(lo.y, sh.y));
                    ql[4] = hsub2(hmul2(lo.z, cl.z), hmul2(hi.z, sl.z)); qh[4] = hadd2(hmul2(hi.z, ch.z), hmul2(lo.z, sh.z));
                    ql[6] = hsub2(hmul2(lo.w, cl.w), hmul2(hi.w, sl.w)); qh[6] = hadd2(hmul2(hi.w, ch.w), hmul2(lo.w, sh.w));
                }
            }
        }

        float s[64], o[kON];
        uint32_t pr[32];
        float ms0, ms1;
        const uint32_t sb4 = (sbase & 0x3FFFF) >> 4;
        const uint64_t dk0 = kDescK | sb4, dv0 = kDescV | (sb4 + (kSmemVOff >> 4));
        const uint32_t id_mine = __shfl_sync(0xffffffffu, 1 + wg, lane), id_other = __shfl_sync(0xffffffffu, 2 - wg, lane);

        {
            float s0[64];
            if (wg == 1) bar_sync(2, 256);
            mbar_wait(bar_full, 0);
            WG_FENCE();
            gemm_qk(s0, q, dk0);
            WG_COMMIT();
            {
                bar_sync(6 + wg, 128);
                const int t = threadIdx.x & 127;
                asm volatile("st.shared.v4.u32 [%0], {%1,%1,%1,%1};" ::"r"(sbase + kSmemVOff + wg * kVSlotBytes + 32768 + (t >> 3) * 1024 + (t & 7) * 144),
                             "r"(0x3F803F80u) : "memory");
                asm volatile("fence.proxy.async.shared::cta;" ::: "memory");
                __syncwarp();
                if (rel) mbar_arrive_cluster(rel_addr + 8 * (2 + wg));
            }
            wg_wait<0>();
            fence_regs(s0);
            bar_arrive(id_other, 256);
            if (rel) mbar_arrive_cluster(rel_addr);
            sched_boundary(p.zero[4]);
            row_max(s0, ms0, ms1);
            ms0 *= kScale; ms1 *= kScale;
            exp_tile<0, kExpSplit0>(s0, ms0, ms1);
            if (wg == 0) exp_tile<kExpSplit0, 16>(s0, ms0, ms1);
            mbar_wait(bar_full + 8, 0);
            bar_sync(id_mine, 256);
            WG_FENCE();
            gemm_qk(s, q, dk0 + (kTileBytes >> 4));
            WG_COMMIT();
            if (wg == 1) exp_tile<kExpSplit0, 16>(s0, ms0, ms1);
            pack_tile(pr, s0);
        }
#pragma unroll
        for (int i = 0; i < kON; i++) o[i] = 0.f;

        uint64_t dk = dk0, dv = dv0;
        auto finish = [&](int j, int ks, int vs, uint32_t vpar, uint32_t z) {
            mbar_wait(bar_full + 16 + 8 * vs, vpar);
            fence_regs(o); fence_regs(pr);
            WG_FENCE();
            gemm_pv(o, pr, dv + vs * (kVSlotBytes >> 4));
            WG_COMMIT();
            bar_arrive(id_other, 256);
            wg_wait<1>();
            fence_regs(s);
            if (rel) mbar_arrive_cluster(rel_addr + 8 * ks);
            exp_tile<0, kExpSplit>(s, ms0, ms1);
            sched_boundary(z);
            wg_wait<0>();
            fence_regs(o); fence_regs(s);
            if (rel) mbar_arrive_cluster(rel_addr + 16 + 8 * vs);
            exp_tile<kExpSplit, 16>(s, ms0, ms1);
            pack_tile(pr, s);
        };
        auto step = [&](int j, int ks, int vs, uint32_t kpar, uint32_t vpar, uint32_t z) {
            mbar_wait(bar_full + 8 * ks, kpar);
            bar_sync(id_mine, 256);
            fence_regs(s);
            WG_FENCE();
            gemm_qk(s, q, dk + ks * (kTileBytes >> 4));
            WG_COMMIT();
            finish(j, ks, vs, vpar, z);
        };
        finish(1, 1, 0, 0, p.zero[2]);
#pragma unroll 1
        for (int i = 1; i < 8; i++) {
            step(2 * i, 0, 1, i, i + 1, p.zero[0]);
            step(2 * i + 1, 1, 0, i, i, p.zero[1]);
            dk += p.zero[0]; dv += p.zero[0];
        }
        asm volatile("barrier.cluster.arrive.relaxed.aligned;" ::: "memory");

        __nv_bfloat16* op = p.out + (h * kS + qt * 128 + warp * 16 + g) * kD + 8 * c;
        bool ok;
        {
            float hi[36], lo[32];
            const float fz = __uint_as_float(p.zero[1]);
#pragma unroll
            for (int i = 0; i < 36; i++) hi[i] = o[32 + i] + fz;
#pragma unroll
            for (int i = 0; i < 32; i++) lo[i] = o[i] + fz;
            mbar_wait(bar_full + 24, 1);
            fence_regs(hi); fence_regs(lo); fence_regs(pr);
            WG_FENCE();
            const uint64_t d = dv0 + (kVSlotBytes >> 4);
#pragma unroll
            for (int kk = 0; kk < 8; kk++) wgmma_pv_hi(hi, pr[4 * kk], pr[4 * kk + 1], pr[4 * kk + 2], pr[4 * kk + 3], d + ((kk * 2048 + 16384) >> 4));
            WG_COMMIT();
#pragma unroll
            for (int kk = 0; kk < 8; kk++) wgmma_pv_lo(lo, pr[4 * kk], pr[4 * kk + 1], pr[4 * kk + 2], pr[4 * kk + 3], d + ((kk * 2048) >> 4));
            WG_COMMIT();
            wg_wait<1>();
            fence_regs(hi);
            const float i0 = rcp(hi[32]), i1 = rcp(hi[34]);
            uint4 u[4], v[4];
            store_half(op + 64, u, hi, 0, i0, i1);
            sched_boundary(p.zero[5]);
            wg_wait<0>();
            fence_regs(lo);
            store_half(op, v, lo, 0, i0, i1);
            sched_boundary(p.zero[6]);
            if (wg == 0) bar_sync(1, 256);
            ok = all_finite(u, v, __shfl_sync(0xffffffffu, 0u, lane)) && hi[32] <= 1.2379400e27f && hi[34] <= 1.2379400e27f;
        }

        if (bar_red_or(3, 256, !ok)) {
            float m0 = -INFINITY, m1 = -INFINITY;
#pragma unroll
            for (int i = 0; i < kON; i++) o[i] = 0.f;
            const uint8_t* src = g_scratch + (size_t)h * kItems * kTileBytes;
#pragma unroll 1
            for (int j = 0; j < 16; j++) {
                if (threadIdx.x == 0) {
                    mbar_expect_tx(bar_fb, 2 * kTileBytes);
                    bulk_g2s(sbase, src + (size_t)(j == 0 ? 0 : 2 * j - 1) * kTileBytes, kTileBytes, bar_fb);
                    bulk_g2s(sbase + kSmemVOff, src + (size_t)(2 * j + 2) * kTileBytes, kTileBytes, bar_fb);
                }
                mbar_wait(bar_fb, j & 1);
                fence_regs(s);
                WG_FENCE();
                gemm_qk(s, q, dk0);
                WG_COMMIT();
                wg_wait<0>();
                fence_regs(s);
                float a0, a1;
                row_max(s, a0, a1);
                a0 = fmaxf(a0, m0); a1 = fmaxf(a1, m1);
                const float r0 = a0 == -INFINITY ? 0.f : a0, r1 = a1 == -INFINITY ? 0.f : a1;
                const float al0 = ex2((m0 - r0) * kScale), al1 = ex2((m1 - r1) * kScale);
                m0 = a0; m1 = a1;
                exp_tile<0, 16>(s, r0 * kScale, r1 * kScale);
                pack_tile(pr, s);
#pragma unroll
                for (int n = 0; n < kON / 4; n++) { o[4 * n] *= al0; o[4 * n + 1] *= al0; o[4 * n + 2] *= al1; o[4 * n + 3] *= al1; }
                fence_regs(o); fence_regs(pr);
                WG_FENCE();
                gemm_pv(o, pr, dv0);
                WG_COMMIT();
                wg_wait<0>();
                fence_regs(o);
                bar_sync(3, 256);
            }
            uint4 v[4];
            store_half(op, v, o, 0, 1.f / o[64], 1.f / o[66]);
            store_half(op + 64, v, o, 32, 1.f / o[64], 1.f / o[66]);
        }
        asm volatile("barrier.cluster.wait.aligned;" ::: "memory");
    }
}

}

extern "C" void kernel_launch(void* const* d_in, const int* in_sizes, int n_in, void* d_out, int out_size) {
    (void)in_sizes; (void)n_in; (void)out_size;
    Params p;
    p.q = (const __nv_bfloat16*)d_in[0];
    p.qk = (const int*)d_in[1];
    p.k_scales = (const __nv_bfloat16*)d_in[2];
    p.k_zeros = (const __nv_bfloat16*)d_in[3];
    p.qv = (const int*)d_in[4];
    p.v_scales = (const __nv_bfloat16*)d_in[5];
    p.v_zeros = (const __nv_bfloat16*)d_in[6];
    p.q_cos = (const __nv_bfloat16*)d_in[7];
    p.q_sin = (const __nv_bfloat16*)d_in[8];
    p.k_cos = (const __nv_bfloat16*)d_in[9];
    p.k_sin = (const __nv_bfloat16*)d_in[10];
    p.out = (__nv_bfloat16*)d_out;
    for (int i = 0; i < 8; i++) p.zero[i] = 0;
    p.t_v0 = 950; p.t_q = 500; p.dt_q = 640; p.t_next = 6000; p.dt_next = 475; p.t_k2 = 2200; p.gap_q = 0; p.k_v1 = 7;
    p.t_poll = 2600; p.stagger = 60; p.lag_q = 140; p.catch_q = 24; p.t_tile1 = 5000; p.t_tile2 = 5800;
    static int co_resident = -1;
    if (co_resident < 0) {
        cudaFuncSetAttribute(attn_kernel, cudaFuncAttributeMaxDynamicSharedMemorySize, kSmemBytes);
        cudaLaunchConfig_t cfg = {};
        cfg.gridDim = dim3(kH * 16); cfg.blockDim = dim3(384); cfg.dynamicSmemBytes = kSmemBytes;
        cudaLaunchAttribute at;
        at.id = cudaLaunchAttributeClusterDimension;
        at.val.clusterDim.x = 2; at.val.clusterDim.y = 1; at.val.clusterDim.z = 1;
        cfg.attrs = &at; cfg.numAttrs = 1;
        int clusters = 0;
        co_resident = cudaOccupancyMaxActiveClusters(&clusters, attn_kernel, &cfg) == cudaSuccess && clusters >= kH * 8;
        (void)cudaGetLastError();
    }
    if (!co_resident) prefill_kernel<<<kItems * kH * 16, 128>>>(p);
    attn_kernel<<<kH * 16, 384, kSmemBytes>>>(p);
}
```

```cpp
#include <cuda_runtime.h>
#include <cuda_bf16.h>
#include <stdint.h>

namespace {

constexpr int kH = 8, kS = 2048, kD = 128;
constexpr int kItems = 33;
constexpr int kTileBytes = 32768;
constexpr int kVSlotBytes = 49152;
constexpr int kDqWarps = 3;
constexpr int kRawBytes = 12288;
constexpr int kSmemVOff = 2 * kTileBytes;
constexpr int kSmemRawOff = kSmemVOff + 2 * kVSlotBytes;
constexpr int kSmemOutOff = kSmemRawOff + kDqWarps * kRawBytes;
constexpr int kSmemScOff = kSmemOutOff + kDqWarps * 2048;
constexpr int kSmemBarOff = kSmemScOff + kDqWarps * 768;
constexpr int kSmemBytes = kSmemBarOff + 512 + 1024;
constexpr int kFlagStride = 64;
constexpr int kON = 68;
constexpr float kScale = 0.08838834764831845f * 1.4426950408889634f;
constexpr uint32_t kWaitLimit = 1u << 30;
constexpr int kExpSplit = 9;
constexpr int kExpSplit0 = 10;

__device__ __align__(1024) uint8_t g_scratch[(size_t)kH * kItems * kTileBytes];
__device__ __align__(256) unsigned g_flags[kH * kItems * kFlagStride];
__device__ unsigned g_done;

struct Params {
    const __nv_bfloat16* q;
    const int* qk;
    const __nv_bfloat16* k_scales;
    const __nv_bfloat16* k_zeros;
    const int* qv;
    const __nv_bfloat16* v_scales;
    const __nv_bfloat16* v_zeros;
    const __nv_bfloat16* q_cos;
    const __nv_bfloat16* q_sin;
    const __nv_bfloat16* k_cos;
    const __nv_bfloat16* k_sin;
    __nv_bfloat16* out;
    uint32_t zero[8];
    int t_v0, t_q, dt_q, t_next, dt_next, t_k2, gap_q, k_v1, t_poll, stagger, lag_q, catch_q, t_tile1, t_tile2;
};

__device__ __forceinline__ uint32_t smem_u32(const void* p) { return (uint32_t)__cvta_generic_to_shared(p); }
__device__ __forceinline__ uint32_t clock32() {
    uint32_t c;
    asm volatile("mov.u32 %0, %%clock;" : "=r"(c));
    return c;
}
__device__ __forceinline__ void wait_until(uint32_t t0, int t) {
    while ((int)(clock32() - t0) < t) {}
    __syncwarp();
}
__device__ __forceinline__ bool elect() {
    uint32_t r;
    asm volatile("{\n.reg .pred p;\nelect.sync _|p, 0xffffffff;\nselp.u32 %0, 1, 0, p;\n}\n" : "=r"(r));
    return r != 0;
}
__device__ __forceinline__ void mbar_init(uint32_t bar, uint32_t count) {
    asm volatile("mbarrier.init.shared::cta.b64 [%0], %1;" ::"r"(bar), "r"(count) : "memory");
}
__device__ __forceinline__ void mbar_expect_tx(uint32_t bar, uint32_t bytes) {
    asm volatile("mbarrier.arrive.expect_tx.shared::cta.b64 _, [%0], %1;" ::"r"(bar), "r"(bytes) : "memory");
}
__device__ __forceinline__ bool mbar_try(uint32_t bar, uint32_t parity) {
    uint32_t ok;
    asm volatile(
        "{\n.reg .pred p;\n"
        "mbarrier.try_wait.parity.shared::cta.b64 p, [%1], %2;\n"
        "selp.u32 %0, 1, 0, p;\n}\n"
        : "=r"(ok)
        : "r"(bar), "r"(parity)
        : "memory");
    return ok != 0;
}
__device__ __forceinline__ void mbar_wait(uint32_t bar, uint32_t parity) {
    if (mbar_try(bar, parity)) return;
    const uint32_t t0 = clock32();
    while (!mbar_try(bar, parity)) {
        if (clock32() - t0 > kWaitLimit) break;
    }
}
__device__ __forceinline__ void mbar_wait_idle(uint32_t bar, uint32_t parity) {
    if (mbar_try(bar, parity)) return;
    const uint32_t t0 = clock32();
    uint32_t ok;
    do {
        asm volatile(
            "{\n.reg .pred p;\n"
            "mbarrier.try_wait.parity.shared::cta.b64 p, [%1], %2, 20000;\n"
            "selp.u32 %0, 1, 0, p;\n}\n"
            : "=r"(ok)
            : "r"(bar), "r"(parity)
            : "memory");
    } while (!ok && clock32() - t0 <= kWaitLimit);
    __syncwarp();
}
__device__ __forceinline__ void mbar_arrive_cluster(uint32_t cluster_addr) {
    asm volatile("mbarrier.arrive.shared::cluster.b64 _, [%0];" ::"r"(cluster_addr) : "memory");
}
__device__ __forceinline__ uint32_t mapa(uint32_t addr, uint32_t rank) {
    uint32_t r;
    asm("mapa.shared::cluster.u32 %0, %1, %2;" : "=r"(r) : "r"(addr), "r"(rank));
    return r;
}
__device__ __forceinline__ void bulk_g2s(uint32_t dst, const void* src, uint32_t bytes, uint32_t bar) {
    asm volatile("cp.async.bulk.shared::cluster.global.mbarrier::complete_tx::bytes [%0], [%1], %2, [%3];" ::"r"(dst),
                 "l"(src), "r"(bytes), "r"(bar)
                 : "memory");
}
__device__ __forceinline__ void bulk_g2s_mc(uint32_t dst, const void* src, uint32_t bytes, uint32_t bar, uint16_t mask) {
    asm volatile(
        "cp.async.bulk.shared::cluster.global.mbarrier::complete_tx::bytes.multicast::cluster [%0], [%1], %2, [%3], %4;" ::"r"(dst),
        "l"(src), "r"(bytes), "r"(bar), "h"(mask)
        : "memory");
}
__device__ __forceinline__ void bar_sync(int id, int n) { asm volatile("bar.sync %0, %1;" ::"r"(id), "r"(n) : "memory"); }
__device__ __forceinline__ void bar_arrive(int id, int n) { asm volatile("bar.arrive %0, %1;" ::"r"(id), "r"(n) : "memory"); }
__device__ __forceinline__ bool bar_red_or(int id, int n, bool v) {
    uint32_t r;
    asm volatile(
        "{\n.reg .pred p, q;\nsetp.ne.u32 q, %3, 0;\n"
        "bar.red.or.pred p, %1, %2, q;\nselp.u32 %0, 1, 0, p;\n}\n"
        : "=r"(r)
        : "r"(id), "r"(n), "r"((uint32_t)v)
        : "memory");
    return r != 0;
}
__device__ __forceinline__ void sched_boundary(uint32_t zero) {
    asm volatile("{\n.reg .pred p;\nsetp.ne.u32 p, %0, 0;\n@p exit;\n}\n" ::"r"(zero) : "memory");
}
__device__ __forceinline__ float ex2(float x) {
    float y;
    asm("ex2.approx.ftz.f32 %0, %1;" : "=f"(y) : "f"(x));
    return y;
}
__device__ __forceinline__ float rcp(float x) {
    float y;
    asm("rcp.approx.ftz.f32 %0, %1;" : "=f"(y) : "f"(x));
    return y;
}
__device__ __forceinline__ uint32_t pack_bf16(float lo, float hi) {
    uint32_t r;
    asm("cvt.rn.bf16x2.f32 %0, %1, %2;" : "=r"(r) : "f"(hi), "f"(lo));
    return r;
}
__device__ __forceinline__ uint32_t hmul2(uint32_t a, uint32_t b) {
    uint32_t r;
    asm("mul.rn.bf16x2 %0, %1, %2;" : "=r"(r) : "r"(a), "r"(b));
    return r;
}
__device__ __forceinline__ uint32_t hadd2(uint32_t a, uint32_t b) {
    uint32_t r;
    asm("add.rn.bf16x2 %0, %1, %2;" : "=r"(r) : "r"(a), "r"(b));
    return r;
}
__device__ __forceinline__ uint32_t hsub2(uint32_t a, uint32_t b) {
    uint32_t r;
    asm("sub.rn.bf16x2 %0, %1, %2;" : "=r"(r) : "r"(a), "r"(b));
    return r;
}
__device__ __forceinline__ uint32_t hfma2(uint32_t a, uint32_t b, uint32_t c) {
    uint32_t r;
    asm("fma.rn.bf16x2 %0, %1, %2, %3;" : "=r"(r) : "r"(a), "r"(b), "r"(c));
    return r;
}
__device__ __forceinline__ uint4 lds128(uint32_t a) {
    uint4 v;
    asm volatile("ld.shared.v4.u32 {%0,%1,%2,%3}, [%4];" : "=r"(v.x), "=r"(v.y), "=r"(v.z), "=r"(v.w) : "r"(a));
    return v;
}
__device__ __forceinline__ uint2 lds64(uint32_t a) {
    uint2 v;
    asm volatile("ld.shared.v2.u32 {%0,%1}, [%2];" : "=r"(v.x), "=r"(v.y) : "r"(a));
    return v;
}
__device__ __forceinline__ uint32_t lds32(uint32_t a) {
    uint32_t v;
    asm volatile("ld.shared.u32 %0, [%1];" : "=r"(v) : "r"(a));
    return v;
}
__device__ __forceinline__ void sts32(uint32_t a, uint32_t v) { asm volatile("st.shared.u32 [%0], %1;" ::"r"(a), "r"(v) : "memory"); }
__device__ __forceinline__ uint4 ldg128(const void* p) {
    uint4 v;
    asm volatile("ld.global.nc.L1::no_allocate.v4.u32 {%0,%1,%2,%3}, [%4];" : "=r"(v.x), "=r"(v.y), "=r"(v.z), "=r"(v.w) : "l"(p) : "memory");
    return v;
}
__device__ __forceinline__ uint2 ldg64(const void* p) {
    uint2 v;
    asm volatile("ld.global.nc.L1::no_allocate.v2.u32 {%0,%1}, [%2];" : "=r"(v.x), "=r"(v.y) : "l"(p) : "memory");
    return v;
}
__device__ __forceinline__ uint32_t ldg32(const void* p) {
    uint32_t v;
    asm volatile("ld.global.nc.L1::no_allocate.u32 %0, [%1];" : "=r"(v) : "l"(p) : "memory");
    return v;
}
__device__ __forceinline__ uint32_t ld_gpu(const void* p) {
    uint32_t v;
    asm volatile("ld.relaxed.gpu.global.u32 %0, [%1];" : "=r"(v) : "l"(p) : "memory");
    return v;
}
__device__ __forceinline__ void red_gpu(unsigned* p, uint32_t v) {
    asm volatile("red.relaxed.gpu.global.add.u32 [%0], %1;" ::"l"(p), "r"(v) : "memory");
}

#define WG_FENCE() asm volatile("wgmma.fence.sync.aligned;" ::: "memory")
#define WG_COMMIT() asm volatile("wgmma.commit_group.sync.aligned;" ::: "memory")
template <int N>
__device__ __forceinline__ void wg_wait() {
    asm volatile("wgmma.wait_group.sync.aligned %0;" ::"n"(N) : "memory");
}
template <int ACC>
__device__ __forceinline__ void wgmma_qk(float (&d)[64], uint32_t a0, uint32_t a1, uint32_t a2, uint32_t a3, uint64_t db) {
    asm volatile(
        "{\n.reg .pred p;\nsetp.ne.b32 p, %69, 0;\n"
        "wgmma.mma_async.sync.aligned.m64n128k16.f32.bf16.bf16 "
        "{%0,%1,%2,%3,%4,%5,%6,%7,%8,%9,%10,%11,%12,%13,%14,%15,%16,%17,%18,%19,%20,%21,%22,%23,"
        "%24,%25,%26,%27,%28,%29,%30,%31,%32,%33,%34,%35,%36,%37,%38,%39,%40,%41,%42,%43,%44,%45,%46,%47,"
        "%48,%49,%50,%51,%52,%53,%54,%55,%56,%57,%58,%59,%60,%61,%62,%63}, {%64,%65,%66,%67}, %68, p, 1, 1, 0;\n}\n"
        : "+f"(d[0]), "+f"(d[1]), "+f"(d[2]), "+f"(d[3]), "+f"(d[4]), "+f"(d[5]), "+f"(d[6]), "+f"(d[7]),
          "+f"(d[8]), "+f"(d[9]), "+f"(d[10]), "+f"(d[11]), "+f"(d[12]), "+f"(d[13]), "+f"(d[14]), "+f"(d[15]),
          "+f"(d[16]), "+f"(d[17]), "+f"(d[18]), "+f"(d[19]), "+f"(d[20]), "+f"(d[21]), "+f"(d[22]), "+f"(d[23]),
          "+f"(d[24]), "+f"(d[25]), "+f"(d[26]), "+f"(d[27]), "+f"(d[28]), "+f"(d[29]), "+f"(d[30]), "+f"(d[31]),
          "+f"(d[32]), "+f"(d[33]), "+f"(d[34]), "+f"(d[35]), "+f"(d[36]), "+f"(d[37]), "+f"(d[38]), "+f"(d[39]),
          "+f"(d[40]), "+f"(d[41]), "+f"(d[42]), "+f"(d[43]), "+f"(d[44]), "+f"(d[45]), "+f"(d[46]), "+f"(d[47]),
          "+f"(d[48]), "+f"(d[49]), "+f"(d[50]), "+f"(d[51]), "+f"(d[52]), "+f"(d[53]), "+f"(d[54]), "+f"(d[55]),
          "+f"(d[56]), "+f"(d[57]), "+f"(d[58]), "+f"(d[59]), "+f"(d[60]), "+f"(d[61]), "+f"(d[62]), "+f"(d[63])
        : "r"(a0), "r"(a1), "r"(a2), "r"(a3), "l"(db), "n"(ACC));
}
__device__ __forceinline__ void wgmma_pv(float (&d)[kON], uint32_t a0, uint32_t a1, uint32_t a2, uint32_t a3, uint64_t db) {
    asm volatile(
        "wgmma.mma_async.sync.aligned.m64n136k16.f32.bf16.bf16 "
        "{%0,%1,%2,%3,%4,%5,%6,%7,%8,%9,%10,%11,%12,%13,%14,%15,%16,%17,%18,%19,%20,%21,%22,%23,"
        "%24,%25,%26,%27,%28,%29,%30,%31,%32,%33,%34,%35,%36,%37,%38,%39,%40,%41,%42,%43,%44,%45,%46,%47,"
        "%48,%49,%50,%51,%52,%53,%54,%55,%56,%57,%58,%59,%60,%61,%62,%63,%64,%65,%66,%67}, {%68,%69,%70,%71}, %72, 1, 1, 1, 1;\n"
        : "+f"(d[0]), "+f"(d[1]), "+f"(d[2]), "+f"(d[3]), "+f"(d[4]), "+f"(d[5]), "+f"(d[6]), "+f"(d[7]),
          "+f"(d[8]), "+f"(d[9]), "+f"(d[10]), "+f"(d[11]), "+f"(d[12]), "+f"(d[13]), "+f"(d[14]), "+f"(d[15]),
          "+f"(d[16]), "+f"(d[17]), "+f"(d[18]), "+f"(d[19]), "+f"(d[20]), "+f"(d[21]), "+f"(d[22]), "+f"(d[23]),
          "+f"(d[24]), "+f"(d[25]), "+f"(d[26]), "+f"(d[27]), "+f"(d[28]), "+f"(d[29]), "+f"(d[30]), "+f"(d[31]),
          "+f"(d[32]), "+f"(d[33]), "+f"(d[34]), "+f"(d[35]), "+f"(d[36]), "+f"(d[37]), "+f"(d[38]), "+f"(d[39]),
          "+f"(d[40]), "+f"(d[41]), "+f"(d[42]), "+f"(d[43]), "+f"(d[44]), "+f"(d[45]), "+f"(d[46]), "+f"(d[47]),
          "+f"(d[48]), "+f"(d[49]), "+f"(d[50]), "+f"(d[51]), "+f"(d[52]), "+f"(d[53]), "+f"(d[54]), "+f"(d[55]),
          "+f"(d[56]), "+f"(d[57]), "+f"(d[58]), "+f"(d[59]), "+f"(d[60]), "+f"(d[61]), "+f"(d[62]), "+f"(d[63]),
          "+f"(d[64]), "+f"(d[65]), "+f"(d[66]), "+f"(d[67])
        : "r"(a0), "r"(a1), "r"(a2), "r"(a3), "l"(db));
}
__device__ __forceinline__ void wgmma_pv_hi(float (&d)[36], uint32_t a0, uint32_t a1, uint32_t a2, uint32_t a3, uint64_t db) {
    asm volatile(
        "wgmma.mma_async.sync.aligned.m64n72k16.f32.bf16.bf16 "
        "{%0,%1,%2,%3,%4,%5,%6,%7,%8,%9,%10,%11,%12,%13,%14,%15,%16,%17,%18,%19,%20,%21,%22,%23,"
        "%24,%25,%26,%27,%28,%29,%30,%31,%32,%33,%34,%35}, {%36,%37,%38,%39}, %40, 1, 1, 1, 1;\n"
        : "+f"(d[0]), "+f"(d[1]), "+f"(d[2]), "+f"(d[3]), "+f"(d[4]), "+f"(d[5]), "+f"(d[6]), "+f"(d[7]),
          "+f"(d[8]), "+f"(d[9]), "+f"(d[10]), "+f"(d[11]), "+f"(d[12]), "+f"(d[13]), "+f"(d[14]), "+f"(d[15]),
          "+f"(d[16]), "+f"(d[17]), "+f"(d[18]), "+f"(d[19]), "+f"(d[20]), "+f"(d[21]), "+f"(d[22]), "+f"(d[23]),
          "+f"(d[24]), "+f"(d[25]), "+f"(d[26]), "+f"(d[27]), "+f"(d[28]), "+f"(d[29]), "+f"(d[30]), "+f"(d[31]),
          "+f"(d[32]), "+f"(d[33]), "+f"(d[34]), "+f"(d[35])
        : "r"(a0), "r"(a1), "r"(a2), "r"(a3), "l"(db));
}
__device__ __forceinline__ void wgmma_pv_lo(float (&d)[32], uint32_t a0, uint32_t a1, uint32_t a2, uint32_t a3, uint64_t db) {
    asm volatile(
        "wgmma.mma_async.sync.aligned.m64n64k16.f32.bf16.bf16 "
        "{%0,%1,%2,%3,%4,%5,%6,%7,%8,%9,%10,%11,%12,%13,%14,%15,%16,%17,%18,%19,%20,%21,%22,%23,"
        "%24,%25,%26,%27,%28,%29,%30,%31}, {%32,%33,%34,%35}, %36, 1, 1, 1, 1;\n"
        : "+f"(d[0]), "+f"(d[1]), "+f"(d[2]), "+f"(d[3]), "+f"(d[4]), "+f"(d[5]), "+f"(d[6]), "+f"(d[7]),
          "+f"(d[8]), "+f"(d[9]), "+f"(d[10]), "+f"(d[11]), "+f"(d[12]), "+f"(d[13]), "+f"(d[14]), "+f"(d[15]),
          "+f"(d[16]), "+f"(d[17]), "+f"(d[18]), "+f"(d[19]), "+f"(d[20]), "+f"(d[21]), "+f"(d[22]), "+f"(d[23]),
          "+f"(d[24]), "+f"(d[25]), "+f"(d[26]), "+f"(d[27]), "+f"(d[28]), "+f"(d[29]), "+f"(d[30]), "+f"(d[31])
        : "r"(a0), "r"(a1), "r"(a2), "r"(a3), "l"(db));
}
template <int N>
__device__ __forceinline__ void fence_regs(float (&d)[N]) {
#pragma unroll
    for (int i = 0; i < N; i++) asm volatile("" : "+f"(d[i])::"memory");
}
__device__ __forceinline__ void fence_regs(uint32_t (&d)[32]) {
#pragma unroll
    for (int i = 0; i < 32; i++) asm volatile("" : "+r"(d[i])::"memory");
}
constexpr uint64_t kDescK = (uint64_t(1) << 62) | (uint64_t(1024 >> 4) << 32) | (uint64_t(1) << 16);
constexpr uint64_t kDescV = (uint64_t(1) << 62) | (uint64_t(1024 >> 4) << 32) | (uint64_t(16384 >> 4) << 16);

__device__ __forceinline__ void gemm_qk(float (&s)[64], const uint32_t (&q)[32], uint64_t d) {
    wgmma_qk<0>(s, q[0], q[1], q[2], q[3], d);
#pragma unroll
    for (int kk = 1; kk < 8; kk++)
        wgmma_qk<1>(s, q[4 * kk], q[4 * kk + 1], q[4 * kk + 2], q[4 * kk + 3], d + (((kk >> 2) * 16384 + (kk & 3) * 32) >> 4));
}
__device__ __forceinline__ void gemm_pv(float (&o)[kON], const uint32_t (&p)[32], uint64_t d) {
#pragma unroll
    for (int kk = 0; kk < 8; kk++) wgmma_pv(o, p[4 * kk], p[4 * kk + 1], p[4 * kk + 2], p[4 * kk + 3], d + ((kk * 2048) >> 4));
}

__device__ __forceinline__ void dequant4(uint32_t (&v)[4], uint32_t sc, uint32_t zp) {
    const uint32_t s0 = __byte_perm(sc, 0, 0x1010), s1 = __byte_perm(sc, 0, 0x3232);
    const uint32_t z0 = __byte_perm(zp, 0, 0x1010), z1 = __byte_perm(zp, 0, 0x3232);
    v[0] = hmul2(hsub2(v[0], z0), s0); v[1] = hmul2(hsub2(v[1], z0), s0);
    v[2] = hmul2(hsub2(v[2], z1), s1); v[3] = hmul2(hsub2(v[3], z1), s1);
}
__device__ __forceinline__ void to_bf16(uint32_t (&v)[4], const uint4& lo, const uint4& hi) {
    v[0] = pack_bf16((float)(int)lo.x, (float)(int)lo.y); v[1] = pack_bf16((float)(int)lo.z, (float)(int)lo.w);
    v[2] = pack_bf16((float)(int)hi.x, (float)(int)hi.y); v[3] = pack_bf16((float)(int)hi.z, (float)(int)hi.w);
}
__device__ __forceinline__ void rope4(uint32_t (&v)[4], const uint2& cl, const uint2& ch, const uint2& sl, const uint2& sh) {
    const uint32_t r0 = hsub2(hmul2(v[0], cl.x), hmul2(v[2], sl.x)), r1 = hsub2(hmul2(v[1], cl.y), hmul2(v[3], sl.y));
    const uint32_t r2 = hadd2(hmul2(v[2], ch.x), hmul2(v[0], sh.x)), r3 = hadd2(hmul2(v[3], ch.y), hmul2(v[1], sh.y));
    v[0] = r0; v[1] = r1; v[2] = r2; v[3] = r3;
}

template <bool IS_V>
__device__ __forceinline__ void dequant_slice(uint32_t ia, uint32_t ca, uint32_t oa, uint32_t sc, uint32_t zp) {
    uint4 lo = lds128(ia), hi = lds128(ia + 256);
#pragma unroll
    for (int it = 0; it < 4; it++) {
        uint2 cl, ch, sl, sh;
        if (!IS_V) {
            const uint32_t a = ca ^ ((it >> 1) * 64 + (it & 1) * 8);
            cl = lds64(a); sl = lds64(a + 2048); ch = lds64(a + 128); sh = lds64(a + 2048 + 128);
        }
        uint32_t v[4];
        to_bf16(v, lo, hi);
        if (it < 3) {
            const uint32_t a = ia ^ (((it + 1) >> 1) * 128 + ((it + 1) & 1) * 16);
            lo = lds128(a); hi = lds128(a + 256);
        }
        dequant4(v, sc, zp);
        if (!IS_V) rope4(v, cl, ch, sl, sh);
        const uint32_t o0 = oa ^ (it << 5), o1 = oa ^ ((it << 5) | 16);
        sts32(o0, v[0]); sts32(o1, v[1]); sts32(o0 + 1024, v[2]); sts32(o1 + 1024, v[3]);
    }
}

struct RowsIn { uint4 lo, hi; uint2 cl, ch, sl, sh; uint32_t sc, zp; };
template <bool IS_V>
__device__ __forceinline__ void rows_load(RowsIn& x, const Params& p, int h, int row, int mp) {
    const int hr = h * kS + row;
    const int* ints = (IS_V ? p.qv : p.qk) + hr * kD + 4 * mp;
    x.lo = ldg128(ints); x.hi = ldg128(ints + 64);
    if (!IS_V) {
        x.cl = ldg64(p.k_cos + row * kD + 4 * mp); x.ch = ldg64(p.k_cos + row * kD + 64 + 4 * mp);
        x.sl = ldg64(p.k_sin + row * kD + 4 * mp); x.sh = ldg64(p.k_sin + row * kD + 64 + 4 * mp);
    }
    x.sc = ldg32((IS_V ? p.v_scales : p.k_scales) + hr * 2); x.zp = ldg32((IS_V ? p.v_zeros : p.k_zeros) + hr * 2);
}
template <bool IS_V>
__device__ __forceinline__ uint8_t* rows_store(const RowsIn& a, uint8_t* slice, int r, int mp) {
    const int j = mp >> 3, c = (mp >> 1) & 3, b = mp & 1;
    uint32_t v[4];
    to_bf16(v, a.lo, a.hi);
    dequant4(v, a.sc, a.zp);
    if (!IS_V) rope4(v, a.cl, a.ch, a.sl, a.sh);
    const bool c0 = c & 1, c1 = c & 2;
    uint32_t x = __shfl_xor_sync(0xffffffffu, c0 ? v[0] : v[1], 2), y = __shfl_xor_sync(0xffffffffu, c0 ? v[2] : v[3], 2);
    const uint32_t a0 = c0 ? x : v[0], a1 = c0 ? v[1] : x, a2 = c0 ? y : v[2], a3 = c0 ? v[3] : y;
    x = __shfl_xor_sync(0xffffffffu, c1 ? a0 : a2, 4); y = __shfl_xor_sync(0xffffffffu, c1 ? a1 : a3, 4);
    uint8_t* dst = slice + (c >> 1) * 16384 + r * 128 + (((4 * j + 2 * b + (c & 1)) ^ r) << 4);
    *reinterpret_cast<uint4*>(dst) = make_uint4(c1 ? x : a0, c1 ? y : a1, c1 ? a2 : x, c1 ? a3 : y);
    return dst;
}

__global__ void __launch_bounds__(128) prefill_kernel(const __grid_constant__ Params p) {
    const int slice = blockIdx.x & 15, h = (blockIdx.x >> 4) & 7, n = blockIdx.x >> 7;
    if (n == kItems - 2) return;
    const int r = threadIdx.x >> 4, mp = threadIdx.x & 15;
    const bool is_v = n != 0 && !(n & 1);
    const int row = (is_v ? (n >> 1) - 1 : (n + 1) >> 1) * 128 + slice * 8 + r;
    uint8_t* dst = g_scratch + (size_t)(h * kItems + n) * kTileBytes + slice * 1024;
    RowsIn x;
    if (is_v) { rows_load<true>(x, p, h, row, mp); rows_store<true>(x, dst, r, mp); }
    else { rows_load<false>(x, p, h, row, mp); rows_store<false>(x, dst, r, mp); }
    if (threadIdx.x == 0 && slice == 0) g_flags[(h * kItems + n) * kFlagStride] = 16;
}

template <int N0, int N1>
__device__ __forceinline__ void exp_tile(float (&s)[64], float ms0, float ms1) {
    if (N0 == 0) {
#pragma unroll
        for (int i = 0; i < 64; i++) s[i] = fmaf(s[i], kScale, (i & 2) ? -ms1 : -ms0);
    }
#pragma unroll
    for (int i = 4 * N0; i < 4 * N1; i++) s[i] = ex2(s[i]);
}
__device__ __forceinline__ void row_max(const float (&s)[64], float& m0, float& m1) {
    float a0 = fmaxf(s[0], s[1]), a1 = fmaxf(s[2], s[3]), b0 = fmaxf(s[4], s[5]), b1 = fmaxf(s[6], s[7]);
#pragma unroll
    for (int n = 2; n < 16; n += 2) {
        a0 = fmaxf(a0, fmaxf(s[4 * n], s[4 * n + 1])); a1 = fmaxf(a1, fmaxf(s[4 * n + 2], s[4 * n + 3]));
        b0 = fmaxf(b0, fmaxf(s[4 * n + 4], s[4 * n + 5])); b1 = fmaxf(b1, fmaxf(s[4 * n + 6], s[4 * n + 7]));
    }
    m0 = fmaxf(a0, b0); m1 = fmaxf(a1, b1);
    m0 = fmaxf(m0, __shfl_xor_sync(0xffffffffu, m0, 1)); m1 = fmaxf(m1, __shfl_xor_sync(0xffffffffu, m1, 1));
    m0 = fmaxf(m0, __shfl_xor_sync(0xffffffffu, m0, 2)); m1 = fmaxf(m1, __shfl_xor_sync(0xffffffffu, m1, 2));
}
__device__ __forceinline__ void pack_tile(uint32_t (&pr)[32], const float (&s)[64]) {
#pragma unroll
    for (int i = 0; i < 32; i++) pr[i] = pack_bf16(s[2 * i], s[2 * i + 1]);
}
template <int N>
__device__ __forceinline__ void store_half(__nv_bfloat16* op, uint4 (&v)[4], const float (&o)[N], int b, float i0, float i1) {
#pragma unroll
    for (int j = 0; j < 2; j++) {
        uint4 &v0 = v[2 * j], &v1 = v[2 * j + 1];
        const float* x = o + b + 16 * j;
        v0.x = pack_bf16(x[0] * i0, x[1] * i0);  v0.y = pack_bf16(x[4] * i0, x[5] * i0);
        v0.z = pack_bf16(x[8] * i0, x[9] * i0);  v0.w = pack_bf16(x[12] * i0, x[13] * i0);
        *reinterpret_cast<uint4*>(op + 32 * j) = v0;
        v1.x = pack_bf16(x[2] * i1, x[3] * i1);  v1.y = pack_bf16(x[6] * i1, x[7] * i1);
        v1.z = pack_bf16(x[10] * i1, x[11] * i1); v1.w = pack_bf16(x[14] * i1, x[15] * i1);
        *reinterpret_cast<uint4*>(op + 8 * kD + 32 * j) = v1;
    }
}
__device__ __forceinline__ bool all_finite(const uint4 (&u)[4], const uint4 (&v)[4], uint32_t zero) {
    uint32_t a[4] = {0, 0, 0, 0};
#pragma unroll
    for (int j = 0; j < 4; j++) {
        a[0] = hfma2(u[j].x, zero, hfma2(v[j].x, zero, a[0])); a[1] = hfma2(u[j].y, zero, hfma2(v[j].y, zero, a[1]));
        a[2] = hfma2(u[j].z, zero, hfma2(v[j].z, zero, a[2])); a[3] = hfma2(u[j].w, zero, hfma2(v[j].w, zero, a[3]));
    }
    return ((a[0] | a[1] | a[2] | a[3]) & 0x7fff7fffu) == 0;
}

template <bool B> struct Tag { static constexpr bool value = B; };

__global__ void __cluster_dims__(2, 1, 1) __launch_bounds__(384, 1) attn_kernel(const __grid_constant__ Params p) {
    extern __shared__ uint8_t smem_raw[];
    const uint32_t sbase = (smem_u32(smem_raw) + 1023) & ~1023u;
    const uint32_t bar_full = sbase + kSmemBarOff;
    const uint32_t bar_empty = bar_full + 32;
    const uint32_t bar_raw = bar_empty + 32;
    const uint32_t bar_q = bar_raw + 16 * kDqWarps;
    const uint32_t bar_fb = bar_q + 128;

    const int h = blockIdx.x >> 4, qt = blockIdx.x & 15;
    const int warp = __shfl_sync(0xffffffffu, threadIdx.x >> 5, 0), lane = threadIdx.x & 31;

    if (warp >= 8) {
        asm volatile("setmaxnreg.dec.sync.aligned.u32 56;");
        if (warp == 8) {
            const uint32_t t0 = clock32();
            const unsigned* fp = g_flags + (h * kItems + lane) * kFlagStride;
            const uint32_t early = ld_gpu(fp);
            if (elect()) {
                for (int i = 0; i < 4; i++) {
                    mbar_init(bar_full + 8 * i, 1);
                    mbar_init(bar_empty + 8 * i, 16);
                }
                mbar_init(bar_fb, 1);
                asm volatile("fence.mbarrier_init.release.cluster;" ::: "memory");
            }
            __syncwarp();
            asm volatile("barrier.cluster.arrive.relaxed.aligned;" ::: "memory");
            asm volatile("barrier.cluster.wait.acquire.aligned;" ::: "memory");
            const uint32_t rank = blockIdx.x & 1;
            const uint8_t* src = g_scratch + (size_t)h * kItems * kTileBytes + rank * (kTileBytes / 2);
            uint32_t ready = __ballot_sync(0xffffffffu, early >= 16);
            asm volatile("fence.acquire.gpu;" ::: "memory");
            uint32_t parity = 3;
            wait_until(t0, p.t_poll);
#pragma unroll 1
            for (int n = 0; n < kItems; n++, ready >>= 1, src += kTileBytes, fp += kFlagStride) {
                if (n == kItems - 2) continue;
                const bool mine = lane < 2 && n + lane < kItems;
                if (!(ready & 1)) {
                    const uint32_t t1 = clock32();
                    do {
                        ready = __ballot_sync(0xffffffffu, mine && ld_gpu(fp) >= 16);
                    } while (!(ready & 1) && !__any_sync(0xffffffffu, clock32() - t1 > kWaitLimit));
                    asm volatile("fence.acquire.gpu;" ::: "memory");
                }
                const bool is_v = n != 0 && !(n & 1);
                const int odd = (((n + 1) >> 1) & 1) ^ (is_v ? 1 : 0);
                const int slot = (is_v ? 2 : 0) + odd;
                const bool peek = !(ready & 2);
                uint32_t ahead = 0;
                if (peek && mine) ahead = ld_gpu(fp);
                if (n == 1) wait_until(t0, p.t_tile1);
                if (n == 2) wait_until(t0, p.t_tile2);
                mbar_wait_idle(bar_empty + 8 * slot, (parity >> slot) & 1);
                if (elect()) {
                    mbar_expect_tx(bar_full + 8 * slot, kTileBytes);
                    const uint32_t dst = sbase + (is_v ? kSmemVOff + odd * kVSlotBytes : odd * kTileBytes);
                    bulk_g2s_mc(dst + rank * (kTileBytes / 2), src, kTileBytes / 2, bar_full + 8 * slot, (uint16_t)3);
                }
                parity ^= 1u << slot;
                if (peek) {
                    ready = __ballot_sync(0xffffffffu, ahead >= 16);
                    asm volatile("fence.acquire.gpu;" ::: "memory");
                }
            }
            uint32_t ticket = 0;
            if (lane == 0) ticket = atomicAdd(&g_done, 1u);
            if (__shfl_sync(0xffffffffu, ticket, 0) == gridDim.x - 1) {
                for (int i = lane; i < kH * kItems; i += 32) g_flags[i * kFlagStride] = 0;
                if (lane == 0) g_done = 0;
            }
        } else {
            const int w = warp - 9;
            const uint32_t t0 = clock32() + p.stagger * h;
            const int first = w == 0 ? 2 : 5 - w;
            const int last = first == 4 ? 28 : kItems - 1;
            const uint32_t my_bar = bar_raw + 16 * w;
            const uint32_t my_raw = sbase + kSmemRawOff + w * kRawBytes;
            const uint32_t my_out = sbase + kSmemOutOff + w * 2048;
            const uint32_t my_sc = sbase + kSmemScOff + w * 768;
            auto fetch = [&](int n, auto tag) {
                constexpr bool V = decltype(tag)::value;
                const int row0 = (V ? (n >> 1) - 1 : (n + 1) >> 1) * 128 + qt * 8;
                if (elect()) {
                    if (V) {
                        mbar_expect_tx(my_bar + 8, 4096);
                        bulk_g2s(my_raw + 8192, p.qv + (h * kS + row0) * kD, 4096, my_bar + 8);
                    } else {
                        mbar_expect_tx(my_bar, 8192);
                        bulk_g2s(my_raw, p.qk + (h * kS + row0) * kD, 4096, my_bar);
                        bulk_g2s(my_raw + 4096, p.k_cos + row0 * kD, 2048, my_bar);
                        bulk_g2s(my_raw + 6144, p.k_sin + row0 * kD, 2048, my_bar);
                    }
                }
            };
            auto fetch_scales = [&](int k) {
                const int n = first + 3 * k;
                const int hr = h * kS + ((n & 1) ? (n + 1) >> 1 : (n >> 1) - 1) * 128 + qt * 8 + (lane & 7);
                const __nv_bfloat16* base = (n & 1) ? ((lane & 8) ? p.k_zeros : p.k_scales) : ((lane & 8) ? p.v_zeros : p.v_scales);
                if (n <= last) asm volatile("cp.async.ca.shared.global [%0], [%1], 4;" ::"r"(my_sc + k * 64 + (lane & 15) * 4), "l"(base + hr * 2) : "memory");
            };
            if (elect()) {
                mbar_init(my_bar, 1); mbar_init(my_bar + 8, 1);
                if (w == 1) for (int i = 0; i < 16; i++) mbar_init(bar_q + 8 * i, 33);
                asm volatile("fence.mbarrier_init.release.cluster;" ::: "memory");
            }
            __syncwarp();
            asm volatile("barrier.cluster.arrive.relaxed.aligned;" ::: "memory");
            fetch_scales(lane >> 4);
            asm volatile("cp.async.commit_group;" ::: "memory");
            if (w == 1) {
#pragma unroll 1
                for (int k = 0; k < 8; k++) {
                    wait_until(t0, p.t_q + h * p.lag_q + k * (p.dt_q - h * p.catch_q) + (k >> 2) * p.gap_q);
#pragma unroll
                    for (int e = 0; e < 2; e++) {
                        const int cw = (k & 4) + (k & 1) * 2 + e, half = (k >> 1) & 1;
                        const int row = qt * 128 + cw * 16 + half * 8;
                        const uint32_t d = sbase + kSmemVOff + (k >> 2) * kVSlotBytes + (cw & 3) * 4096 + half * 2048, bar = bar_q + 16 * cw + 8 * half;
                        const uint32_t dl = d + ((lane * 16) ^ ((lane & 16) << 2));
                        const uint8_t* sl = (const uint8_t*)(p.q + (h * kS + row) * kD + lane * 8);
#pragma unroll
                        for (int i = 0; i < 4; i++)
                            asm volatile("cp.async.cg.shared.global [%0], [%1], 16;" ::"r"(dl + i * 512), "l"(sl + i * 512) : "memory");
                        asm volatile("cp.async.mbarrier.arrive.noinc.shared::cta.b64 [%0];" ::"r"(bar) : "memory");
                        if (elect()) {
                            mbar_expect_tx(bar, 4096);
                            bulk_g2s(d + 16384, p.q_cos + row * kD, 2048, bar);
                            bulk_g2s(d + 32768, p.q_sin + row * kD, 2048, bar);
                        }
                    }
                    if (k == p.k_v1) fetch(4, Tag<true>{});
                }
            } else {
                wait_until(t0, w == 0 ? p.t_v0 : p.t_k2);
                if (w == 0) fetch(2, Tag<true>{}); else fetch(3, Tag<false>{});
            }
            const int r = lane >> 2, c = lane & 3, x = r & 3;
            const uint32_t ia = my_raw + r * 512 + c * 32 + (x >> 1) * 128 + (x & 1) * 16;
            const uint32_t ca = my_raw + 4096 + r * 256 + c * 16 + (x >> 1) * 64 + (x & 1) * 8;
            const uint32_t oa = my_out + r * 128 + c * 4 + (((2 * x) ^ r) << 4);
            const int back = (lane & 16) * 1024 + (lane & 15) * 64 - lane * 16;
            uint8_t* dst = g_scratch + (size_t)(h * kItems + first) * kTileBytes + qt * 1024 + lane * 16;
            uint32_t sa = my_sc + r * 4;
            auto convert = [&](int n, auto tag) {
                constexpr bool V = decltype(tag)::value;
                dequant_slice<V>(ia + (V ? 8192 : 0), ca, oa, lds32(sa), lds32(sa + 32));
                __syncwarp();
                const uint4 v0 = lds128(my_out + lane * 16), v1 = lds128(my_out + 512 + lane * 16);
                const uint4 v2 = lds128(my_out + 1024 + lane * 16), v3 = lds128(my_out + 1536 + lane * 16);
                uint4* d = reinterpret_cast<uint4*>(dst);
                d[0] = v0; d[32] = v1; d[1024] = v2; d[1056] = v3;
                return ld_gpu(dst + back);
            };
            auto publish = [&](int n, uint32_t seen) {
                const uint32_t one = 1u + (__reduce_or_sync(0xffffffffu, seen) & p.zero[0]);
                if (elect()) red_gpu(g_flags + (h * kItems + n) * kFlagStride, one);
                dst += (size_t)kDqWarps * kTileBytes;
                sa += 64;
            };
            auto round0 = [&](auto tag) {
                constexpr bool V = decltype(tag)::value;
                asm volatile("cp.async.wait_group 0;" ::: "memory");
                mbar_wait_idle(my_bar + (V ? 8 : 0), 0);
                __syncwarp();
                const uint32_t seen = convert(first, tag);
                const int due = p.t_next + (first - 2) * p.dt_next;
                const bool soon = __any_sync(0xffffffffu, (int)(clock32() - t0) + 800 >= due);
                if (!soon) publish(first, seen);
                wait_until(t0, due);
                fetch(first + kDqWarps, Tag<!V>{});
                if (soon) publish(first, seen);
            };
            if (first & 1) round0(Tag<false>{}); else round0(Tag<true>{});
#pragma unroll 1
            for (int k = 2; k < 12; k += 2) fetch_scales(k + (lane >> 4));
            asm volatile("cp.async.commit_group;" ::: "memory");
            uint32_t round = 1;
            auto item = [&](int n, auto tag) {
                constexpr bool V = decltype(tag)::value;
                mbar_wait_idle(my_bar + (V ? 8 : 0), round >> 1);
                if (n + kDqWarps <= last) fetch(n + kDqWarps, Tag<!V>{});
                const uint32_t seen = convert(n, tag);
                asm volatile("cp.async.wait_group 0;" ::: "memory");
                publish(n, seen);
            };
#pragma unroll 1
            for (int n = first + kDqWarps; n <= last; n += kDqWarps, round++) {
                if (n & 1) item(n, Tag<false>{}); else item(n, Tag<true>{});
            }
            asm volatile("barrier.cluster.wait.aligned;" ::: "memory");
        }
    } else {
        const int wg = warp >> 2;
        const int g = lane >> 2, c = lane & 3;
        RowsIn kin;
        rows_load<false>(kin, p, h, wg * 128 + qt * 8 + 2 * (warp & 3) + (lane >> 4), lane & 15);
        asm volatile("barrier.cluster.arrive.relaxed.aligned;" ::: "memory");
        asm volatile("setmaxnreg.inc.sync.aligned.u32 224;");
        {
            const uint8_t* at = rows_store<false>(kin, g_scratch + (size_t)(h * kItems + wg) * kTileBytes + qt * 1024,
                                                  2 * (warp & 3) + (lane >> 4), lane & 15);
            const bool never = bar_red_or(4 + wg, 128, (ld_gpu(at) & p.zero[0]) != 0);
            if ((warp & 3) == 0 && elect()) red_gpu(g_flags + (h * kItems + wg) * kFlagStride, never ? 0u : 1u);
        }
        const uint32_t rel_addr = mapa(bar_empty, lane & 1);
        const bool rel = lane < 2;
        asm volatile("barrier.cluster.wait.acquire.aligned;" ::: "memory");
        if (rel) mbar_arrive_cluster(rel_addr + 8 * (3 - wg));

        uint32_t q[32];
        {
            const uint32_t a = sbase + kSmemVOff + wg * kVSlotBytes + (warp & 3) * 4096 + g * 256 + c * 16;
#pragma unroll
            for (int r = 0; r < 2; r++) {
                mbar_wait(bar_q + 16 * warp + 8 * r, 0);
#pragma unroll
                for (int j = 0; j < 2; j++) {
                    const uint32_t bq = a + r * 2048 + ((j * 64) ^ ((g & 1) * 64)), bt = a + r * 2048 + j * 64;
                    const uint4 lo = lds128(bq), hi = lds128(bq + 128);
                    const uint4 cl = lds128(bt + 16384), ch = lds128(bt + 16384 + 128);
                    const uint4 sl = lds128(bt + 32768), sh = lds128(bt + 32768 + 128);
                    uint32_t* ql = q + 8 * j + r;
                    uint32_t* qh = ql + 16;
                    ql[0] = hsub2(hmul2(lo.x, cl.x), hmul2(hi.x, sl.x)); qh[0] = hadd2(hmul2(hi.x, ch.x), hmul2(lo.x, sh.x));
                    ql[2] = hsub2(hmul2(lo.y, cl.y), hmul2(hi.y, sl.y)); qh[2] = hadd2(hmul2(hi.y, ch.y), hmul2(lo.y, sh.y));
                    ql[4] = hsub2(hmul2(lo.z, cl.z), hmul2(hi.z, sl.z)); qh[4] = hadd2(hmul2(hi.z, ch.z), hmul2(lo.z, sh.z));
                    ql[6] = hsub2(hmul2(lo.w, cl.w), hmul2(hi.w, sl.w)); qh[6] = hadd2(hmul2(hi.w, ch.w), hmul2(lo.w, sh.w));
                }
            }
        }

        float s[64], o[kON];
        uint32_t pr[32];
        float ms0, ms1;
        const uint32_t sb4 = (sbase & 0x3FFFF) >> 4;
        const uint64_t dk0 = kDescK | sb4, dv0 = kDescV | (sb4 + (kSmemVOff >> 4));
        const uint32_t id_mine = __shfl_sync(0xffffffffu, 1 + wg, lane), id_other = __shfl_sync(0xffffffffu, 2 - wg, lane);

        {
            float s0[64];
            if (wg == 1) bar_sync(2, 256);
            mbar_wait(bar_full, 0);
            WG_FENCE();
            gemm_qk(s0, q, dk0);
            WG_COMMIT();
            {
                bar_sync(6 + wg, 128);
                const int t = threadIdx.x & 127;
                asm volatile("st.shared.v4.u32 [%0], {%1,%1,%1,%1};" ::"r"(sbase + kSmemVOff + wg * kVSlotBytes + 32768 + (t >> 3) * 1024 + (t & 7) * 144),
                             "r"(0x3F803F80u) : "memory");
                asm volatile("fence.proxy.async.shared::cta;" ::: "memory");
                __syncwarp();
                if (rel) mbar_arrive_cluster(rel_addr + 8 * (2 + wg));
            }
            wg_wait<0>();
            fence_regs(s0);
            bar_arrive(id_other, 256);
            if (rel) mbar_arrive_cluster(rel_addr);
            sched_boundary(p.zero[4]);
            row_max(s0, ms0, ms1);
            ms0 *= kScale; ms1 *= kScale;
            exp_tile<0, kExpSplit0>(s0, ms0, ms1);
            if (wg == 0) exp_tile<kExpSplit0, 16>(s0, ms0, ms1);
            mbar_wait(bar_full + 8, 0);
            bar_sync(id_mine, 256);
            WG_FENCE();
            gemm_qk(s, q, dk0 + (kTileBytes >> 4));
            WG_COMMIT();
            if (wg == 1) exp_tile<kExpSplit0, 16>(s0, ms0, ms1);
            pack_tile(pr, s0);
        }
#pragma unroll
        for (int i = 0; i < kON; i++) o[i] = 0.f;

        uint64_t dk = dk0, dv = dv0;
        auto finish = [&](int j, int ks, int vs, uint32_t vpar, uint32_t z) {
            mbar_wait(bar_full + 16 + 8 * vs, vpar);
            fence_regs(o); fence_regs(pr);
            WG_FENCE();
            gemm_pv(o, pr, dv + vs * (kVSlotBytes >> 4));
            WG_COMMIT();
            bar_arrive(id_other, 256);
            wg_wait<1>();
            fence_regs(s);
            if (rel) mbar_arrive_cluster(rel_addr + 8 * ks);
            exp_tile<0, kExpSplit>(s, ms0, ms1);
            sched_boundary(z);
            wg_wait<0>();
            fence_regs(o); fence_regs(s);
            if (rel) mbar_arrive_cluster(rel_addr + 16 + 8 * vs);
            exp_tile<kExpSplit, 16>(s, ms0, ms1);
            pack_tile(pr, s);
        };
        auto step = [&](int j, int ks, int vs, uint32_t kpar, uint32_t vpar, uint32_t z) {
            mbar_wait(bar_full + 8 * ks, kpar);
            bar_sync(id_mine, 256);
            fence_regs(s);
            WG_FENCE();
            gemm_qk(s, q, dk + ks * (kTileBytes >> 4));
            WG_COMMIT();
            finish(j, ks, vs, vpar, z);
        };
        finish(1, 1, 0, 0, p.zero[2]);
#pragma unroll 1
        for (int i = 1; i < 8; i++) {
            step(2 * i, 0, 1, i, i + 1, p.zero[0]);
            step(2 * i + 1, 1, 0, i, i, p.zero[1]);
            dk += p.zero[0]; dv += p.zero[0];
        }
        asm volatile("barrier.cluster.arrive.relaxed.aligned;" ::: "memory");

        __nv_bfloat16* op = p.out + (h * kS + qt * 128 + warp * 16 + g) * kD + 8 * c;
        bool ok;
        {
            float hi[36], lo[32];
            const float fz = __uint_as_float(p.zero[1]);
#pragma unroll
            for (int i = 0; i < 36; i++) hi[i] = o[32 + i] + fz;
#pragma unroll
            for (int i = 0; i < 32; i++) lo[i] = o[i] + fz;
            mbar_wait(bar_full + 24, 1);
            fence_regs(hi); fence_regs(lo); fence_regs(pr);
            WG_FENCE();
            const uint64_t d = dv0 + (kVSlotBytes >> 4);
#pragma unroll
            for (int kk = 0; kk < 8; kk++) wgmma_pv_hi(hi, pr[4 * kk], pr[4 * kk + 1], pr[4 * kk + 2], pr[4 * kk + 3], d + ((kk * 2048 + 16384) >> 4));
            WG_COMMIT();
#pragma unroll
            for (int kk = 0; kk < 8; kk++) wgmma_pv_lo(lo, pr[4 * kk], pr[4 * kk + 1], pr[4 * kk + 2], pr[4 * kk + 3], d + ((kk * 2048) >> 4));
            WG_COMMIT();
            wg_wait<1>();
            fence_regs(hi);
            const float i0 = rcp(hi[32]), i1 = rcp(hi[34]);
            uint4 u[4], v[4];
            store_half(op + 64, u, hi, 0, i0, i1);
            sched_boundary(p.zero[5]);
            wg_wait<0>();
            fence_regs(lo);
            store_half(op, v, lo, 0, i0, i1);
            sched_boundary(p.zero[6]);
            if (wg == 0) bar_sync(1, 256);
            ok = all_finite(u, v, __shfl_sync(0xffffffffu, 0u, lane)) && fminf(hi[32], hi[34]) >= 0.5f && hi[32] <= 1.2379400e27f &&
                 hi[34] <= 1.2379400e27f;
        }

        if (bar_red_or(3, 256, !ok)) {
            float m0 = -INFINITY, m1 = -INFINITY;
#pragma unroll
            for (int i = 0; i < kON; i++) o[i] = 0.f;
            const uint8_t* src = g_scratch + (size_t)h * kItems * kTileBytes;
#pragma unroll 1
            for (int j = 0; j < 16; j++) {
                if (threadIdx.x == 0) {
                    mbar_expect_tx(bar_fb, 2 * kTileBytes);
                    bulk_g2s(sbase, src + (size_t)(j == 0 ? 0 : 2 * j - 1) * kTileBytes, kTileBytes, bar_fb);
                    bulk_g2s(sbase + kSmemVOff, src + (size_t)(2 * j + 2) * kTileBytes, kTileBytes, bar_fb);
                }
                mbar_wait(bar_fb, j & 1);
                fence_regs(s);
                WG_FENCE();
                gemm_qk(s, q, dk0);
                WG_COMMIT();
                wg_wait<0>();
                fence_regs(s);
                float a0, a1;
                row_max(s, a0, a1);
                a0 = fmaxf(a0, m0); a1 = fmaxf(a1, m1);
                const float r0 = a0 == -INFINITY ? 0.f : a0, r1 = a1 == -INFINITY ? 0.f : a1;
                const float al0 = ex2((m0 - r0) * kScale), al1 = ex2((m1 - r1) * kScale);
                m0 = a0; m1 = a1;
#pragma unroll
                for (int i = 0; i < 64; i++) s[i] = ex2((s[i] - ((i & 2) ? r1 : r0)) * kScale);
                pack_tile(pr, s);
#pragma unroll
                for (int n = 0; n < kON / 4; n++) { o[4 * n] *= al0; o[4 * n + 1] *= al0; o[4 * n + 2] *= al1; o[4 * n + 3] *= al1; }
                fence_regs(o); fence_regs(pr);
                WG_FENCE();
                gemm_pv(o, pr, dv0);
                WG_COMMIT();
                wg_wait<0>();
                fence_regs(o);
                bar_sync(3, 256);
            }
            uint4 v[4];
            store_half(op, v, o, 0, 1.f / o[64], 1.f / o[66]);
            store_half(op + 64, v, o, 32, 1.f / o[64], 1.f / o[66]);
        }
        asm volatile("barrier.cluster.wait.aligned;" ::: "memory");
    }
}

}

extern "C" void kernel_launch(void* const* d_in, const int* in_sizes, int n_in, void* d_out, int out_size) {
    (void)in_sizes; (void)n_in; (void)out_size;
    Params p;
    p.q = (const __nv_bfloat16*)d_in[0];
    p.qk = (const int*)d_in[1];
    p.k_scales = (const __nv_bfloat16*)d_in[2];
    p.k_zeros = (const __nv_bfloat16*)d_in[3];
    p.qv = (const int*)d_in[4];
    p.v_scales = (const __nv_bfloat16*)d_in[5];
    p.v_zeros = (const __nv_bfloat16*)d_in[6];
    p.q_cos = (const __nv_bfloat16*)d_in[7];
    p.q_sin = (const __nv_bfloat16*)d_in[8];
    p.k_cos = (const __nv_bfloat16*)d_in[9];
    p.k_sin = (const __nv_bfloat16*)d_in[10];
    p.out = (__nv_bfloat16*)d_out;
    for (int i = 0; i < 8; i++) p.zero[i] = 0;
    p.t_v0 = 950; p.t_q = 500; p.dt_q = 640; p.t_next = 6000; p.dt_next = 475; p.t_k2 = 2200; p.gap_q = 0; p.k_v1 = 7;
    p.t_poll = 2600; p.stagger = 60; p.lag_q = 140; p.catch_q = 24; p.t_tile1 = 5000; p.t_tile2 = 5800;
    static int co_resident = -1;
    if (co_resident < 0) {
        cudaFuncSetAttribute(attn_kernel, cudaFuncAttributeMaxDynamicSharedMemorySize, kSmemBytes);
        cudaLaunchConfig_t cfg = {};
        cfg.gridDim = dim3(kH * 16); cfg.blockDim = dim3(384); cfg.dynamicSmemBytes = kSmemBytes;
        cudaLaunchAttribute at;
        at.id = cudaLaunchAttributeClusterDimension;
        at.val.clusterDim.x = 2; at.val.clusterDim.y = 1; at.val.clusterDim.z = 1;
        cfg.attrs = &at; cfg.numAttrs = 1;
        int clusters = 0;
        co_resident = cudaOccupancyMaxActiveClusters(&clusters, attn_kernel, &cfg) == cudaSuccess && clusters >= kH * 8;
        (void)cudaGetLastError();
    }
    if (!co_resident) prefill_kernel<<<kItems * kH * 16, 128>>>(p);
    attn_kernel<<<kH * 16, 384, kSmemBytes>>>(p);
}
```

```cpp
#include <cuda_runtime.h>
#include <cuda_bf16.h>
#include <stdint.h>

namespace {

constexpr int kH = 8, kS = 2048, kD = 128;
constexpr int kItems = 33;
constexpr int kTileBytes = 32768;
constexpr int kVSlotBytes = 49152;
constexpr int kDqWarps = 3;
constexpr int kRawBytes = 12288;
constexpr int kSmemVOff = 2 * kTileBytes;
constexpr int kSmemRawOff = kSmemVOff + 2 * kVSlotBytes;
constexpr int kSmemOutOff = kSmemRawOff + kDqWarps * kRawBytes;
constexpr int kSmemScOff = kSmemOutOff + kDqWarps * 2048;
constexpr int kSmemBarOff = kSmemScOff + kDqWarps * 768;
constexpr int kSmemBytes = kSmemBarOff + 512 + 1024;
constexpr int kFlagStride = 64;
constexpr int kON = 68;
constexpr float kScale = 0.08838834764831845f * 1.4426950408889634f;
constexpr uint32_t kWaitLimit = 1u << 30;
constexpr int kExpSplit = 9;
constexpr int kExpSplit0 = 10;

__device__ __align__(1024) uint8_t g_scratch[(size_t)kH * kItems * kTileBytes];
__device__ __align__(256) unsigned g_flags[kH * kItems * kFlagStride];
__device__ unsigned g_done;

struct Params {
    const __nv_bfloat16* q;
    const int* qk;
    const __nv_bfloat16* k_scales;
    const __nv_bfloat16* k_zeros;
    const int* qv;
    const __nv_bfloat16* v_scales;
    const __nv_bfloat16* v_zeros;
    const __nv_bfloat16* q_cos;
    const __nv_bfloat16* q_sin;
    const __nv_bfloat16* k_cos;
    const __nv_bfloat16* k_sin;
    __nv_bfloat16* out;
    uint32_t zero[8];
    int t_v0, t_q, dt_q, t_next, dt_next, t_k2, t_poll, stagger, lag_q, catch_q, t_tile1, t_tile2;
};

__device__ __forceinline__ uint32_t smem_u32(const void* p) { return (uint32_t)__cvta_generic_to_shared(p); }
__device__ __forceinline__ uint32_t clock32() {
    uint32_t c;
    asm volatile("mov.u32 %0, %%clock;" : "=r"(c));
    return c;
}
__device__ __forceinline__ void wait_until(uint32_t t0, int t) {
    while ((int)(clock32() - t0) < t) {}
    __syncwarp();
}
__device__ __forceinline__ bool elect() {
    uint32_t r;
    asm volatile("{\n.reg .pred p;\nelect.sync _|p, 0xffffffff;\nselp.u32 %0, 1, 0, p;\n}\n" : "=r"(r));
    return r != 0;
}
__device__ __forceinline__ void mbar_init(uint32_t bar, uint32_t count) {
    asm volatile("mbarrier.init.shared::cta.b64 [%0], %1;" ::"r"(bar), "r"(count) : "memory");
}
__device__ __forceinline__ void mbar_expect_tx(uint32_t bar, uint32_t bytes) {
    asm volatile("mbarrier.arrive.expect_tx.shared::cta.b64 _, [%0], %1;" ::"r"(bar), "r"(bytes) : "memory");
}
__device__ __forceinline__ bool mbar_try(uint32_t bar, uint32_t parity) {
    uint32_t ok;
    asm volatile(
        "{\n.reg .pred p;\n"
        "mbarrier.try_wait.parity.shared::cta.b64 p, [%1], %2;\n"
        "selp.u32 %0, 1, 0, p;\n}\n"
        : "=r"(ok)
        : "r"(bar), "r"(parity)
        : "memory");
    return ok != 0;
}
__device__ __forceinline__ void mbar_wait(uint32_t bar, uint32_t parity) {
    if (mbar_try(bar, parity)) return;
    const uint32_t t0 = clock32();
    while (!mbar_try(bar, parity)) {
        if (clock32() - t0 > kWaitLimit) break;
    }
}
__device__ __forceinline__ void mbar_wait_idle(uint32_t bar, uint32_t parity) {
    if (mbar_try(bar, parity)) return;
    const uint32_t t0 = clock32();
    uint32_t ok;
    do {
        asm volatile(
            "{\n.reg .pred p;\n"
            "mbarrier.try_wait.parity.shared::cta.b64 p, [%1], %2, 20000;\n"
            "selp.u32 %0, 1, 0, p;\n}\n"
            : "=r"(ok)
            : "r"(bar), "r"(parity)
            : "memory");
    } while (!ok && clock32() - t0 <= kWaitLimit);
    __syncwarp();
}
__device__ __forceinline__ void mbar_arrive_cluster(uint32_t cluster_addr) {
    asm volatile("mbarrier.arrive.shared::cluster.b64 _, [%0];" ::"r"(cluster_addr) : "memory");
}
__device__ __forceinline__ uint32_t mapa(uint32_t addr, uint32_t rank) {
    uint32_t r;
    asm("mapa.shared::cluster.u32 %0, %1, %2;" : "=r"(r) : "r"(addr), "r"(rank));
    return r;
}
__device__ __forceinline__ void bulk_g2s(uint32_t dst, const void* src, uint32_t bytes, uint32_t bar) {
    asm volatile("cp.async.bulk.shared::cluster.global.mbarrier::complete_tx::bytes [%0], [%1], %2, [%3];" ::"r"(dst),
                 "l"(src), "r"(bytes), "r"(bar)
                 : "memory");
}
__device__ __forceinline__ void bulk_g2s_mc(uint32_t dst, const void* src, uint32_t bytes, uint32_t bar, uint16_t mask) {
    asm volatile(
        "cp.async.bulk.shared::cluster.global.mbarrier::complete_tx::bytes.multicast::cluster [%0], [%1], %2, [%3], %4;" ::"r"(dst),
        "l"(src), "r"(bytes), "r"(bar), "h"(mask)
        : "memory");
}
__device__ __forceinline__ void bar_sync(int id, int n) { asm volatile("bar.sync %0, %1;" ::"r"(id), "r"(n) : "memory"); }
__device__ __forceinline__ void bar_arrive(int id, int n) { asm volatile("bar.arrive %0, %1;" ::"r"(id), "r"(n) : "memory"); }
__device__ __forceinline__ bool bar_red_or(int id, int n, bool v) {
    uint32_t r;
    asm volatile(
        "{\n.reg .pred p, q;\nsetp.ne.u32 q, %3, 0;\n"
        "bar.red.or.pred p, %1, %2, q;\nselp.u32 %0, 1, 0, p;\n}\n"
        : "=r"(r)
        : "r"(id), "r"(n), "r"((uint32_t)v)
        : "memory");
    return r != 0;
}
__device__ __forceinline__ void sched_boundary(uint32_t zero) {
    asm volatile("{\n.reg .pred p;\nsetp.ne.u32 p, %0, 0;\n@p exit;\n}\n" ::"r"(zero) : "memory");
}
__device__ __forceinline__ float ex2(float x) {
    float y;
    asm("ex2.approx.ftz.f32 %0, %1;" : "=f"(y) : "f"(x));
    return y;
}
__device__ __forceinline__ float rcp(float x) {
    float y;
    asm("rcp.approx.ftz.f32 %0, %1;" : "=f"(y) : "f"(x));
    return y;
}
__device__ __forceinline__ uint32_t pack_bf16(float lo, float hi) {
    uint32_t r;
    asm("cvt.rn.bf16x2.f32 %0, %1, %2;" : "=r"(r) : "f"(hi), "f"(lo));
    return r;
}
__device__ __forceinline__ uint32_t hmul2(uint32_t a, uint32_t b) {
    uint32_t r;
    asm("mul.rn.bf16x2 %0, %1, %2;" : "=r"(r) : "r"(a), "r"(b));
    return r;
}
__device__ __forceinline__ uint32_t hadd2(uint32_t a, uint32_t b) {
    uint32_t r;
    asm("add.rn.bf16x2 %0, %1, %2;" : "=r"(r) : "r"(a), "r"(b));
    return r;
}
__device__ __forceinline__ uint32_t hsub2(uint32_t a, uint32_t b) {
    uint32_t r;
    asm("sub.rn.bf16x2 %0, %1, %2;" : "=r"(r) : "r"(a), "r"(b));
    return r;
}
__device__ __forceinline__ uint32_t hfma2(uint32_t a, uint32_t b, uint32_t c) {
    uint32_t r;
    asm("fma.rn.bf16x2 %0, %1, %2, %3;" : "=r"(r) : "r"(a), "r"(b), "r"(c));
    return r;
}
__device__ __forceinline__ uint4 lds128(uint32_t a) {
    uint4 v;
    asm volatile("ld.shared.v4.u32 {%0,%1,%2,%3}, [%4];" : "=r"(v.x), "=r"(v.y), "=r"(v.z), "=r"(v.w) : "r"(a));
    return v;
}
__device__ __forceinline__ uint2 lds64(uint32_t a) {
    uint2 v;
    asm volatile("ld.shared.v2.u32 {%0,%1}, [%2];" : "=r"(v.x), "=r"(v.y) : "r"(a));
    return v;
}
__device__ __forceinline__ uint32_t lds32(uint32_t a) {
    uint32_t v;
    asm volatile("ld.shared.u32 %0, [%1];" : "=r"(v) : "r"(a));
    return v;
}
__device__ __forceinline__ void sts32(uint32_t a, uint32_t v) { asm volatile("st.shared.u32 [%0], %1;" ::"r"(a), "r"(v) : "memory"); }
__device__ __forceinline__ uint4 ldg128(const void* p) {
    uint4 v;
    asm volatile("ld.global.nc.L1::no_allocate.v4.u32 {%0,%1,%2,%3}, [%4];" : "=r"(v.x), "=r"(v.y), "=r"(v.z), "=r"(v.w) : "l"(p) : "memory");
    return v;
}
__device__ __forceinline__ uint2 ldg64(const void* p) {
    uint2 v;
    asm volatile("ld.global.nc.L1::no_allocate.v2.u32 {%0,%1}, [%2];" : "=r"(v.x), "=r"(v.y) : "l"(p) : "memory");
    return v;
}
__device__ __forceinline__ uint32_t ldg32(const void* p) {
    uint32_t v;
    asm volatile("ld.global.nc.L1::no_allocate.u32 %0, [%1];" : "=r"(v) : "l"(p) : "memory");
    return v;
}
__device__ __forceinline__ uint32_t ld_gpu(const void* p) {
    uint32_t v;
    asm volatile("ld.relaxed.gpu.global.u32 %0, [%1];" : "=r"(v) : "l"(p) : "memory");
    return v;
}
__device__ __forceinline__ void red_gpu(unsigned* p, uint32_t v) {
    asm volatile("red.relaxed.gpu.global.add.u32 [%0], %1;" ::"l"(p), "r"(v) : "memory");
}

#define WG_FENCE() asm volatile("wgmma.fence.sync.aligned;" ::: "memory")
#define WG_COMMIT() asm volatile("wgmma.commit_group.sync.aligned;" ::: "memory")
template <int N>
__device__ __forceinline__ void wg_wait() {
    asm volatile("wgmma.wait_group.sync.aligned %0;" ::"n"(N) : "memory");
}
template <int ACC>
__device__ __forceinline__ void wgmma_qk(float (&d)[64], uint32_t a0, uint32_t a1, uint32_t a2, uint32_t a3, uint64_t db) {
    asm volatile(
        "{\n.reg .pred p;\nsetp.ne.b32 p, %69, 0;\n"
        "wgmma.mma_async.sync.aligned.m64n128k16.f32.bf16.bf16 "
        "{%0,%1,%2,%3,%4,%5,%6,%7,%8,%9,%10,%11,%12,%13,%14,%15,%16,%17,%18,%19,%20,%21,%22,%23,"
        "%24,%25,%26,%27,%28,%29,%30,%31,%32,%33,%34,%35,%36,%37,%38,%39,%40,%41,%42,%43,%44,%45,%46,%47,"
        "%48,%49,%50,%51,%52,%53,%54,%55,%56,%57,%58,%59,%60,%61,%62,%63}, {%64,%65,%66,%67}, %68, p, 1, 1, 0;\n}\n"
        : "+f"(d[0]), "+f"(d[1]), "+f"(d[2]), "+f"(d[3]), "+f"(d[4]), "+f"(d[5]), "+f"(d[6]), "+f"(d[7]),
          "+f"(d[8]), "+f"(d[9]), "+f"(d[10]), "+f"(d[11]), "+f"(d[12]), "+f"(d[13]), "+f"(d[14]), "+f"(d[15]),
          "+f"(d[16]), "+f"(d[17]), "+f"(d[18]), "+f"(d[19]), "+f"(d[20]), "+f"(d[21]), "+f"(d[22]), "+f"(d[23]),
          "+f"(d[24]), "+f"(d[25]), "+f"(d[26]), "+f"(d[27]), "+f"(d[28]), "+f"(d[29]), "+f"(d[30]), "+f"(d[31]),
          "+f"(d[32]), "+f"(d[33]), "+f"(d[34]), "+f"(d[35]), "+f"(d[36]), "+f"(d[37]), "+f"(d[38]), "+f"(d[39]),
          "+f"(d[40]), "+f"(d[41]), "+f"(d[42]), "+f"(d[43]), "+f"(d[44]), "+f"(d[45]), "+f"(d[46]), "+f"(d[47]),
          "+f"(d[48]), "+f"(d[49]), "+f"(d[50]), "+f"(d[51]), "+f"(d[52]), "+f"(d[53]), "+f"(d[54]), "+f"(d[55]),
          "+f"(d[56]), "+f"(d[57]), "+f"(d[58]), "+f"(d[59]), "+f"(d[60]), "+f"(d[61]), "+f"(d[62]), "+f"(d[63])
        : "r"(a0), "r"(a1), "r"(a2), "r"(a3), "l"(db), "n"(ACC));
}
__device__ __forceinline__ void wgmma_pv(float (&d)[kON], uint32_t a0, uint32_t a1, uint32_t a2, uint32_t a3, uint64_t db) {
    asm volatile(
        "wgmma.mma_async.sync.aligned.m64n136k16.f32.bf16.bf16 "
        "{%0,%1,%2,%3,%4,%5,%6,%7,%8,%9,%10,%11,%12,%13,%14,%15,%16,%17,%18,%19,%20,%21,%22,%23,"
        "%24,%25,%26,%27,%28,%29,%30,%31,%32,%33,%34,%35,%36,%37,%38,%39,%40,%41,%42,%43,%44,%45,%46,%47,"
        "%48,%49,%50,%51,%52,%53,%54,%55,%56,%57,%58,%59,%60,%61,%62,%63,%64,%65,%66,%67}, {%68,%69,%70,%71}, %72, 1, 1, 1, 1;\n"
        : "+f"(d[0]), "+f"(d[1]), "+f"(d[2]), "+f"(d[3]), "+f"(d[4]), "+f"(d[5]), "+f"(d[6]), "+f"(d[7]),
          "+f"(d[8]), "+f"(d[9]), "+f"(d[10]), "+f"(d[11]), "+f"(d[12]), "+f"(d[13]), "+f"(d[14]), "+f"(d[15]),
          "+f"(d[16]), "+f"(d[17]), "+f"(d[18]), "+f"(d[19]), "+f"(d[20]), "+f"(d[21]), "+f"(d[22]), "+f"(d[23]),
          "+f"(d[24]), "+f"(d[25]), "+f"(d[26]), "+f"(d[27]), "+f"(d[28]), "+f"(d[29]), "+f"(d[30]), "+f"(d[31]),
          "+f"(d[32]), "+f"(d[33]), "+f"(d[34]), "+f"(d[35]), "+f"(d[36]), "+f"(d[37]), "+f"(d[38]), "+f"(d[39]),
          "+f"(d[40]), "+f"(d[41]), "+f"(d[42]), "+f"(d[43]), "+f"(d[44]), "+f"(d[45]), "+f"(d[46]), "+f"(d[47]),
          "+f"(d[48]), "+f"(d[49]), "+f"(d[50]), "+f"(d[51]), "+f"(d[52]), "+f"(d[53]), "+f"(d[54]), "+f"(d[55]),
          "+f"(d[56]), "+f"(d[57]), "+f"(d[58]), "+f"(d[59]), "+f"(d[60]), "+f"(d[61]), "+f"(d[62]), "+f"(d[63]),
          "+f"(d[64]), "+f"(d[65]), "+f"(d[66]), "+f"(d[67])
        : "r"(a0), "r"(a1), "r"(a2), "r"(a3), "l"(db));
}
__device__ __forceinline__ void wgmma_pv_hi(float (&d)[36], uint32_t a0, uint32_t a1, uint32_t a2, uint32_t a3, uint64_t db) {
    asm volatile(
        "wgmma.mma_async.sync.aligned.m64n72k16.f32.bf16.bf16 "
        "{%0,%1,%2,%3,%4,%5,%6,%7,%8,%9,%10,%11,%12,%13,%14,%15,%16,%17,%18,%19,%20,%21,%22,%23,"
        "%24,%25,%26,%27,%28,%29,%30,%31,%32,%33,%34,%35}, {%36,%37,%38,%39}, %40, 1, 1, 1, 1;\n"
        : "+f"(d[0]), "+f"(d[1]), "+f"(d[2]), "+f"(d[3]), "+f"(d[4]), "+f"(d[5]), "+f"(d[6]), "+f"(d[7]),
          "+f"(d[8]), "+f"(d[9]), "+f"(d[10]), "+f"(d[11]), "+f"(d[12]), "+f"(d[13]), "+f"(d[14]), "+f"(d[15]),
          "+f"(d[16]), "+f"(d[17]), "+f"(d[18]), "+f"(d[19]), "+f"(d[20]), "+f"(d[21]), "+f"(d[22]), "+f"(d[23]),
          "+f"(d[24]), "+f"(d[25]), "+f"(d[26]), "+f"(d[27]), "+f"(d[28]), "+f"(d[29]), "+f"(d[30]), "+f"(d[31]),
          "+f"(d[32]), "+f"(d[33]), "+f"(d[34]), "+f"(d[35])
        : "r"(a0), "r"(a1), "r"(a2), "r"(a3), "l"(db));
}
__device__ __forceinline__ void wgmma_pv_lo(float (&d)[32], uint32_t a0, uint32_t a1, uint32_t a2, uint32_t a3, uint64_t db) {
    asm volatile(
        "wgmma.mma_async.sync.aligned.m64n64k16.f32.bf16.bf16 "
        "{%0,%1,%2,%3,%4,%5,%6,%7,%8,%9,%10,%11,%12,%13,%14,%15,%16,%17,%18,%19,%20,%21,%22,%23,"
        "%24,%25,%26,%27,%28,%29,%30,%31}, {%32,%33,%34,%35}, %36, 1, 1, 1, 1;\n"
        : "+f"(d[0]), "+f"(d[1]), "+f"(d[2]), "+f"(d[3]), "+f"(d[4]), "+f"(d[5]), "+f"(d[6]), "+f"(d[7]),
          "+f"(d[8]), "+f"(d[9]), "+f"(d[10]), "+f"(d[11]), "+f"(d[12]), "+f"(d[13]), "+f"(d[14]), "+f"(d[15]),
          "+f"(d[16]), "+f"(d[17]), "+f"(d[18]), "+f"(d[19]), "+f"(d[20]), "+f"(d[21]), "+f"(d[22]), "+f"(d[23]),
          "+f"(d[24]), "+f"(d[25]), "+f"(d[26]), "+f"(d[27]), "+f"(d[28]), "+f"(d[29]), "+f"(d[30]), "+f"(d[31])
        : "r"(a0), "r"(a1), "r"(a2), "r"(a3), "l"(db));
}
template <int N>
__device__ __forceinline__ void fence_regs(float (&d)[N]) {
#pragma unroll
    for (int i = 0; i < N; i++) asm volatile("" : "+f"(d[i])::"memory");
}
__device__ __forceinline__ void fence_regs(uint32_t (&d)[32]) {
#pragma unroll
    for (int i = 0; i < 32; i++) asm volatile("" : "+r"(d[i])::"memory");
}
constexpr uint64_t kDescK = (uint64_t(1) << 62) | (uint64_t(1024 >> 4) << 32) | (uint64_t(1) << 16);
constexpr uint64_t kDescV = (uint64_t(1) << 62) | (uint64_t(1024 >> 4) << 32) | (uint64_t(16384 >> 4) << 16);

__device__ __forceinline__ void gemm_qk(float (&s)[64], const uint32_t (&q)[32], uint64_t d) {
    wgmma_qk<0>(s, q[0], q[1], q[2], q[3], d);
#pragma unroll
    for (int kk = 1; kk < 8; kk++)
        wgmma_qk<1>(s, q[4 * kk], q[4 * kk + 1], q[4 * kk + 2], q[4 * kk + 3], d + (((kk >> 2) * 16384 + (kk & 3) * 32) >> 4));
}
__device__ __forceinline__ void gemm_pv(float (&o)[kON], const uint32_t (&p)[32], uint64_t d) {
#pragma unroll
    for (int kk = 0; kk < 8; kk++) wgmma_pv(o, p[4 * kk], p[4 * kk + 1], p[4 * kk + 2], p[4 * kk + 3], d + ((kk * 2048) >> 4));
}

__device__ __forceinline__ void dequant4(uint32_t (&v)[4], uint32_t sc, uint32_t zp) {
    const uint32_t s0 = __byte_perm(sc, 0, 0x1010), s1 = __byte_perm(sc, 0, 0x3232);
    const uint32_t z0 = __byte_perm(zp, 0, 0x1010), z1 = __byte_perm(zp, 0, 0x3232);
    v[0] = hmul2(hsub2(v[0], z0), s0); v[1] = hmul2(hsub2(v[1], z0), s0);
    v[2] = hmul2(hsub2(v[2], z1), s1); v[3] = hmul2(hsub2(v[3], z1), s1);
}
__device__ __forceinline__ void to_bf16(uint32_t (&v)[4], const uint4& lo, const uint4& hi) {
    v[0] = pack_bf16((float)(int)lo.x, (float)(int)lo.y); v[1] = pack_bf16((float)(int)lo.z, (float)(int)lo.w);
    v[2] = pack_bf16((float)(int)hi.x, (float)(int)hi.y); v[3] = pack_bf16((float)(int)hi.z, (float)(int)hi.w);
}
__device__ __forceinline__ void rope4(uint32_t (&v)[4], const uint2& cl, const uint2& ch, const uint2& sl, const uint2& sh) {
    const uint32_t r0 = hsub2(hmul2(v[0], cl.x), hmul2(v[2], sl.x)), r1 = hsub2(hmul2(v[1], cl.y), hmul2(v[3], sl.y));
    const uint32_t r2 = hadd2(hmul2(v[2], ch.x), hmul2(v[0], sh.x)), r3 = hadd2(hmul2(v[3], ch.y), hmul2(v[1], sh.y));
    v[0] = r0; v[1] = r1; v[2] = r2; v[3] = r3;
}

template <bool IS_V>
__device__ __forceinline__ void dequant_slice(uint32_t ia, uint32_t ca, uint32_t oa, uint32_t sc, uint32_t zp) {
    uint4 lo = lds128(ia), hi = lds128(ia + 256);
#pragma unroll
    for (int it = 0; it < 4; it++) {
        uint2 cl, ch, sl, sh;
        if (!IS_V) {
            const uint32_t a = ca ^ ((it >> 1) * 64 + (it & 1) * 8);
            cl = lds64(a); sl = lds64(a + 2048); ch = lds64(a + 128); sh = lds64(a + 2048 + 128);
        }
        uint32_t v[4];
        to_bf16(v, lo, hi);
        if (it < 3) {
            const uint32_t a = ia ^ (((it + 1) >> 1) * 128 + ((it + 1) & 1) * 16);
            lo = lds128(a); hi = lds128(a + 256);
        }
        dequant4(v, sc, zp);
        if (!IS_V) rope4(v, cl, ch, sl, sh);
        const uint32_t o0 = oa ^ (it << 5), o1 = oa ^ ((it << 5) | 16);
        sts32(o0, v[0]); sts32(o1, v[1]); sts32(o0 + 1024, v[2]); sts32(o1 + 1024, v[3]);
    }
}

struct RowsIn { uint4 lo, hi; uint2 cl, ch, sl, sh; uint32_t sc, zp; };
template <bool IS_V>
__device__ __forceinline__ void rows_load(RowsIn& x, const Params& p, int h, int row, int mp) {
    const int hr = h * kS + row;
    const int* ints = (IS_V ? p.qv : p.qk) + hr * kD + 4 * mp;
    x.lo = ldg128(ints); x.hi = ldg128(ints + 64);
    if (!IS_V) {
        x.cl = ldg64(p.k_cos + row * kD + 4 * mp); x.ch = ldg64(p.k_cos + row * kD + 64 + 4 * mp);
        x.sl = ldg64(p.k_sin + row * kD + 4 * mp); x.sh = ldg64(p.k_sin + row * kD + 64 + 4 * mp);
    }
    x.sc = ldg32((IS_V ? p.v_scales : p.k_scales) + hr * 2); x.zp = ldg32((IS_V ? p.v_zeros : p.k_zeros) + hr * 2);
}
template <bool IS_V>
__device__ __forceinline__ uint8_t* rows_store(const RowsIn& a, uint8_t* slice, int r, int mp) {
    const int j = mp >> 3, c = (mp >> 1) & 3, b = mp & 1;
    uint32_t v[4];
    to_bf16(v, a.lo, a.hi);
    dequant4(v, a.sc, a.zp);
    if (!IS_V) rope4(v, a.cl, a.ch, a.sl, a.sh);
    const bool c0 = c & 1, c1 = c & 2;
    uint32_t x = __shfl_xor_sync(0xffffffffu, c0 ? v[0] : v[1], 2), y = __shfl_xor_sync(0xffffffffu, c0 ? v[2] : v[3], 2);
    const uint32_t a0 = c0 ? x : v[0], a1 = c0 ? v[1] : x, a2 = c0 ? y : v[2], a3 = c0 ? v[3] : y;
    x = __shfl_xor_sync(0xffffffffu, c1 ? a0 : a2, 4); y = __shfl_xor_sync(0xffffffffu, c1 ? a1 : a3, 4);
    uint8_t* dst = slice + (c >> 1) * 16384 + r * 128 + (((4 * j + 2 * b + (c & 1)) ^ r) << 4);
    *reinterpret_cast<uint4*>(dst) = make_uint4(c1 ? x : a0, c1 ? y : a1, c1 ? a2 : x, c1 ? a3 : y);
    return dst;
}

__global__ void __launch_bounds__(128) prefill_kernel(const __grid_constant__ Params p) {
    const int slice = blockIdx.x & 15, h = (blockIdx.x >> 4) & 7, n = blockIdx.x >> 7;
    if (n == kItems - 2) return;
    const int r = threadIdx.x >> 4, mp = threadIdx.x & 15;
    const bool is_v = n != 0 && !(n & 1);
    const int row = (is_v ? (n >> 1) - 1 : (n + 1) >> 1) * 128 + slice * 8 + r;
    uint8_t* dst = g_scratch + (size_t)(h * kItems + n) * kTileBytes + slice * 1024;
    RowsIn x;
    if (is_v) { rows_load<true>(x, p, h, row, mp); rows_store<true>(x, dst, r, mp); }
    else { rows_load<false>(x, p, h, row, mp); rows_store<false>(x, dst, r, mp); }
    if (threadIdx.x == 0 && slice == 0) g_flags[(h * kItems + n) * kFlagStride] = 16;
}

template <int N0, int N1>
__device__ __forceinline__ void exp_tile(float (&s)[64], float ms0, float ms1) {
    if (N0 == 0) {
#pragma unroll
        for (int i = 0; i < 64; i++) s[i] = fmaf(s[i], kScale, (i & 2) ? -ms1 : -ms0);
    }
#pragma unroll
    for (int i = 4 * N0; i < 4 * N1; i++) s[i] = ex2(s[i]);
}
__device__ __forceinline__ void row_max(const float (&s)[64], float& m0, float& m1) {
    float a0 = fmaxf(s[0], s[1]), a1 = fmaxf(s[2], s[3]), b0 = fmaxf(s[4], s[5]), b1 = fmaxf(s[6], s[7]);
#pragma unroll
    for (int n = 2; n < 16; n += 2) {
        a0 = fmaxf(a0, fmaxf(s[4 * n], s[4 * n + 1])); a1 = fmaxf(a1, fmaxf(s[4 * n + 2], s[4 * n + 3]));
        b0 = fmaxf(b0, fmaxf(s[4 * n + 4], s[4 * n + 5])); b1 = fmaxf(b1, fmaxf(s[4 * n + 6], s[4 * n + 7]));
    }
    m0 = fmaxf(a0, b0); m1 = fmaxf(a1, b1);
    m0 = fmaxf(m0, __shfl_xor_sync(0xffffffffu, m0, 1)); m1 = fmaxf(m1, __shfl_xor_sync(0xffffffffu, m1, 1));
    m0 = fmaxf(m0, __shfl_xor_sync(0xffffffffu, m0, 2)); m1 = fmaxf(m1, __shfl_xor_sync(0xffffffffu, m1, 2));
}
__device__ __forceinline__ void pack_tile(uint32_t (&pr)[32], const float (&s)[64]) {
#pragma unroll
    for (int i = 0; i < 32; i++) pr[i] = pack_bf16(s[2 * i], s[2 * i + 1]);
}
template <int N>
__device__ __forceinline__ void store_half(__nv_bfloat16* op, uint4 (&v)[4], const float (&o)[N], int b, float i0, float i1) {
#pragma unroll
    for (int j = 0; j < 2; j++) {
        uint4 &v0 = v[2 * j], &v1 = v[2 * j + 1];
        const float* x = o + b + 16 * j;
        v0.x = pack_bf16(x[0] * i0, x[1] * i0);  v0.y = pack_bf16(x[4] * i0, x[5] * i0);
        v0.z = pack_bf16(x[8] * i0, x[9] * i0);  v0.w = pack_bf16(x[12] * i0, x[13] * i0);
        *reinterpret_cast<uint4*>(op + 32 * j) = v0;
        v1.x = pack_bf16(x[2] * i1, x[3] * i1);  v1.y = pack_bf16(x[6] * i1, x[7] * i1);
        v1.z = pack_bf16(x[10] * i1, x[11] * i1); v1.w = pack_bf16(x[14] * i1, x[15] * i1);
        *reinterpret_cast<uint4*>(op + 8 * kD + 32 * j) = v1;
    }
}
__device__ __forceinline__ bool all_finite(const uint4 (&u)[4], const uint4 (&v)[4], uint32_t zero) {
    uint32_t a[4] = {0, 0, 0, 0};
#pragma unroll
    for (int j = 0; j < 4; j++) {
        a[0] = hfma2(u[j].x, zero, hfma2(v[j].x, zero, a[0])); a[1] = hfma2(u[j].y, zero, hfma2(v[j].y, zero, a[1]));
        a[2] = hfma2(u[j].z, zero, hfma2(v[j].z, zero, a[2])); a[3] = hfma2(u[j].w, zero, hfma2(v[j].w, zero, a[3]));
    }
    return ((a[0] | a[1] | a[2] | a[3]) & 0x7fff7fffu) == 0;
}

template <bool B> struct Tag { static constexpr bool value = B; };

__global__ void __cluster_dims__(2, 1, 1) __launch_bounds__(384, 1) attn_kernel(const __grid_constant__ Params p) {
    extern __shared__ uint8_t smem_raw[];
    const uint32_t sbase = (smem_u32(smem_raw) + 1023) & ~1023u;
    const uint32_t bar_full = sbase + kSmemBarOff;
    const uint32_t bar_empty = bar_full + 32;
    const uint32_t bar_raw = bar_empty + 32;
    const uint32_t bar_q = bar_raw + 16 * kDqWarps;
    const uint32_t bar_fb = bar_q + 128;

    const int h = blockIdx.x >> 4, qt = blockIdx.x & 15;
    const int warp = __shfl_sync(0xffffffffu, threadIdx.x >> 5, 0), lane = threadIdx.x & 31;

    if (warp >= 8) {
        asm volatile("setmaxnreg.dec.sync.aligned.u32 56;");
        if (warp == 8) {
            const uint32_t t0 = clock32();
            const unsigned* fp = g_flags + (h * kItems + lane) * kFlagStride;
            const uint32_t early = ld_gpu(fp);
            if (elect()) {
                for (int i = 0; i < 4; i++) {
                    mbar_init(bar_full + 8 * i, 1);
                    mbar_init(bar_empty + 8 * i, 16);
                }
                mbar_init(bar_fb, 1);
                asm volatile("fence.mbarrier_init.release.cluster;" ::: "memory");
            }
            __syncwarp();
            asm volatile("barrier.cluster.arrive.relaxed.aligned;" ::: "memory");
            asm volatile("barrier.cluster.wait.acquire.aligned;" ::: "memory");
            const uint32_t rank = blockIdx.x & 1;
            const uint8_t* src = g_scratch + (size_t)h * kItems * kTileBytes + rank * (kTileBytes / 2);
            uint32_t ready = __ballot_sync(0xffffffffu, early >= 16);
            asm volatile("fence.acquire.gpu;" ::: "memory");
            uint32_t parity = 3;
            wait_until(t0, p.t_poll);
#pragma unroll 1
            for (int n = 0; n < kItems; n++, ready >>= 1, src += kTileBytes, fp += kFlagStride) {
                if (n == kItems - 2) continue;
                const bool mine = lane < 2 && n + lane < kItems;
                if (!(ready & 1)) {
                    const uint32_t t1 = clock32();
                    do {
                        ready = __ballot_sync(0xffffffffu, mine && ld_gpu(fp) >= 16);
                    } while (!(ready & 1) && !__any_sync(0xffffffffu, clock32() - t1 > kWaitLimit));
                    asm volatile("fence.acquire.gpu;" ::: "memory");
                }
                const bool is_v = n != 0 && !(n & 1);
                const int odd = (((n + 1) >> 1) & 1) ^ (is_v ? 1 : 0);
                const int slot = (is_v ? 2 : 0) + odd;
                const bool peek = !(ready & 2);
                uint32_t ahead = 0;
                if (peek && mine) ahead = ld_gpu(fp);
                if (n == 1) wait_until(t0, p.t_tile1);
                if (n == 2) wait_until(t0, p.t_tile2);
                mbar_wait_idle(bar_empty + 8 * slot, (parity >> slot) & 1);
                if (elect()) {
                    mbar_expect_tx(bar_full + 8 * slot, kTileBytes);
                    const uint32_t dst = sbase + (is_v ? kSmemVOff + odd * kVSlotBytes : odd * kTileBytes);
                    bulk_g2s_mc(dst + rank * (kTileBytes / 2), src, kTileBytes / 2, bar_full + 8 * slot, (uint16_t)3);
                }
                parity ^= 1u << slot;
                if (peek) {
                    ready = __ballot_sync(0xffffffffu, ahead >= 16);
                    asm volatile("fence.acquire.gpu;" ::: "memory");
                }
            }
            uint32_t ticket = 0;
            if (lane == 0) ticket = atomicAdd(&g_done, 1u);
            if (__shfl_sync(0xffffffffu, ticket, 0) == gridDim.x - 1) {
                for (int i = lane; i < kH * kItems; i += 32) g_flags[i * kFlagStride] = 0;
                if (lane == 0) g_done = 0;
            }
        } else {
            const int w = warp - 9;
            const uint32_t t0 = clock32() + p.stagger * h;
            const int first = w == 0 ? 2 : 5 - w;
            const int last = first == 4 ? 28 : kItems - 1;
            const uint32_t my_bar = bar_raw + 16 * w;
            const uint32_t my_raw = sbase + kSmemRawOff + w * kRawBytes;
            const uint32_t my_out = sbase + kSmemOutOff + w * 2048;
            const uint32_t my_sc = sbase + kSmemScOff + w * 768;
            auto fetch = [&](int n, auto tag) {
                constexpr bool V = decltype(tag)::value;
                const int row0 = (V ? (n >> 1) - 1 : (n + 1) >> 1) * 128 + qt * 8;
                if (elect()) {
                    if (V) {
                        mbar_expect_tx(my_bar + 8, 4096);
                        bulk_g2s(my_raw + 8192, p.qv + (h * kS + row0) * kD, 4096, my_bar + 8);
                    } else {
                        mbar_expect_tx(my_bar, 8192);
                        bulk_g2s(my_raw, p.qk + (h * kS + row0) * kD, 4096, my_bar);
                        bulk_g2s(my_raw + 4096, p.k_cos + row0 * kD, 2048, my_bar);
                        bulk_g2s(my_raw + 6144, p.k_sin + row0 * kD, 2048, my_bar);
                    }
                }
            };
            auto fetch_scales = [&](int k) {
                const int n = first + 3 * k;
                const int hr = h * kS + ((n & 1) ? (n + 1) >> 1 : (n >> 1) - 1) * 128 + qt * 8 + (lane & 7);
                const __nv_bfloat16* base = (n & 1) ? ((lane & 8) ? p.k_zeros : p.k_scales) : ((lane & 8) ? p.v_zeros : p.v_scales);
                if (n <= last) asm volatile("cp.async.ca.shared.global [%0], [%1], 4;" ::"r"(my_sc + k * 64 + (lane & 15) * 4), "l"(base + hr * 2) : "memory");
            };
            if (elect()) {
                mbar_init(my_bar, 1); mbar_init(my_bar + 8, 1);
                if (w == 1) for (int i = 0; i < 16; i++) mbar_init(bar_q + 8 * i, 33);
                asm volatile("fence.mbarrier_init.release.cluster;" ::: "memory");
            }
            __syncwarp();
            asm volatile("barrier.cluster.arrive.relaxed.aligned;" ::: "memory");
            fetch_scales(lane >> 4);
            asm volatile("cp.async.commit_group;" ::: "memory");
            if (w == 1) {
#pragma unroll 1
                for (int k = 0; k < 8; k++) {
                    wait_until(t0, p.t_q + h * p.lag_q + k * (p.dt_q - h * p.catch_q));
#pragma unroll
                    for (int e = 0; e < 2; e++) {
                        const int cw = (k & 4) + (k & 1) * 2 + e, half = (k >> 1) & 1;
                        const int row = qt * 128 + cw * 16 + half * 8;
                        const uint32_t d = sbase + kSmemVOff + (k >> 2) * kVSlotBytes + (cw & 3) * 4096 + half * 2048, bar = bar_q + 16 * cw + 8 * half;
                        const uint32_t dl = d + ((lane * 16) ^ ((lane & 16) << 2));
                        const uint8_t* sl = (const uint8_t*)(p.q + (h * kS + row) * kD + lane * 8);
#pragma unroll
                        for (int i = 0; i < 4; i++)
                            asm volatile("cp.async.cg.shared.global [%0], [%1], 16;" ::"r"(dl + i * 512), "l"(sl + i * 512) : "memory");
                        asm volatile("cp.async.mbarrier.arrive.noinc.shared::cta.b64 [%0];" ::"r"(bar) : "memory");
                        if (elect()) {
                            mbar_expect_tx(bar, 4096);
                            bulk_g2s(d + 16384, p.q_cos + row * kD, 2048, bar);
                            bulk_g2s(d + 32768, p.q_sin + row * kD, 2048, bar);
                        }
                    }
                }
                fetch(4, Tag<true>{});
            } else {
                wait_until(t0, w == 0 ? p.t_v0 : p.t_k2);
                if (w == 0) fetch(2, Tag<true>{}); else fetch(3, Tag<false>{});
            }
            const int r = lane >> 2, c = lane & 3, x = r & 3;
            const uint32_t ia = my_raw + r * 512 + c * 32 + (x >> 1) * 128 + (x & 1) * 16;
            const uint32_t ca = my_raw + 4096 + r * 256 + c * 16 + (x >> 1) * 64 + (x & 1) * 8;
            const uint32_t oa = my_out + r * 128 + c * 4 + (((2 * x) ^ r) << 4);
            const int back = (lane & 16) * 1024 + (lane & 15) * 64 - lane * 16;
            uint8_t* dst = g_scratch + (size_t)(h * kItems + first) * kTileBytes + qt * 1024 + lane * 16;
            uint32_t sa = my_sc + r * 4;
            auto convert = [&](int n, auto tag) {
                constexpr bool V = decltype(tag)::value;
                dequant_slice<V>(ia + (V ? 8192 : 0), ca, oa, lds32(sa), lds32(sa + 32));
                __syncwarp();
                const uint4 v0 = lds128(my_out + lane * 16), v1 = lds128(my_out + 512 + lane * 16);
                const uint4 v2 = lds128(my_out + 1024 + lane * 16), v3 = lds128(my_out + 1536 + lane * 16);
                uint4* d = reinterpret_cast<uint4*>(dst);
                d[0] = v0; d[32] = v1; d[1024] = v2; d[1056] = v3;
                return ld_gpu(dst + back);
            };
            auto publish = [&](int n, uint32_t seen) {
                const uint32_t one = 1u + (__reduce_or_sync(0xffffffffu, seen) & p.zero[0]);
                if (elect()) red_gpu(g_flags + (h * kItems + n) * kFlagStride, one);
                dst += (size_t)kDqWarps * kTileBytes;
                sa += 64;
            };
            auto round0 = [&](auto tag) {
                constexpr bool V = decltype(tag)::value;
                asm volatile("cp.async.wait_group 0;" ::: "memory");
                mbar_wait_idle(my_bar + (V ? 8 : 0), 0);
                __syncwarp();
                const uint32_t seen = convert(first, tag);
                const int due = p.t_next + (first - 2) * p.dt_next;
                const bool soon = __any_sync(0xffffffffu, (int)(clock32() - t0) + 800 >= due);
                if (!soon) publish(first, seen);
                wait_until(t0, due);
                fetch(first + kDqWarps, Tag<!V>{});
                if (soon) publish(first, seen);
            };
            if (first & 1) round0(Tag<false>{}); else round0(Tag<true>{});
#pragma unroll 1
            for (int k = 2; k < 12; k += 2) fetch_scales(k + (lane >> 4));
            asm volatile("cp.async.commit_group;" ::: "memory");
            uint32_t round = 1;
            auto item = [&](int n, auto tag) {
                constexpr bool V = decltype(tag)::value;
                mbar_wait_idle(my_bar + (V ? 8 : 0), round >> 1);
                if (n + kDqWarps <= last) fetch(n + kDqWarps, Tag<!V>{});
                const uint32_t seen = convert(n, tag);
                asm volatile("cp.async.wait_group 0;" ::: "memory");
                publish(n, seen);
            };
#pragma unroll 1
            for (int n = first + kDqWarps; n <= last; n += kDqWarps, round++) {
                if (n & 1) item(n, Tag<false>{}); else item(n, Tag<true>{});
            }
            asm volatile("barrier.cluster.wait.aligned;" ::: "memory");
        }
    } else {
        const int wg = warp >> 2;
        const int g = lane >> 2, c = lane & 3;
        RowsIn kin;
        rows_load<false>(kin, p, h, wg * 128 + qt * 8 + 2 * (warp & 3) + (lane >> 4), lane & 15);
        asm volatile("barrier.cluster.arrive.relaxed.aligned;" ::: "memory");
        asm volatile("setmaxnreg.inc.sync.aligned.u32 224;");
        {
            const uint8_t* at = rows_store<false>(kin, g_scratch + (size_t)(h * kItems + wg) * kTileBytes + qt * 1024,
                                                  2 * (warp & 3) + (lane >> 4), lane & 15);
            const bool never = bar_red_or(4 + wg, 128, (ld_gpu(at) & p.zero[0]) != 0);
            if ((warp & 3) == 0 && elect()) red_gpu(g_flags + (h * kItems + wg) * kFlagStride, never ? 0u : 1u);
        }
        const uint32_t rel_addr = mapa(bar_empty, lane & 1);
        const bool rel = lane < 2;
        asm volatile("barrier.cluster.wait.acquire.aligned;" ::: "memory");
        if (rel) mbar_arrive_cluster(rel_addr + 8 * (3 - wg));

        uint32_t q[32];
        {
            const uint32_t a = sbase + kSmemVOff + wg * kVSlotBytes + (warp & 3) * 4096 + g * 256 + c * 16;
#pragma unroll
            for (int r = 0; r < 2; r++) {
                mbar_wait(bar_q + 16 * warp + 8 * r, 0);
#pragma unroll
                for (int j = 0; j < 2; j++) {
                    const uint32_t bq = a + r * 2048 + ((j * 64) ^ ((g & 1) * 64)), bt = a + r * 2048 + j * 64;
                    const uint4 lo = lds128(bq), hi = lds128(bq + 128);
                    const uint4 cl = lds128(bt + 16384), ch = lds128(bt + 16384 + 128);
                    const uint4 sl = lds128(bt + 32768), sh = lds128(bt + 32768 + 128);
                    uint32_t* ql = q + 8 * j + r;
                    uint32_t* qh = ql + 16;
                    ql[0] = hsub2(hmul2(lo.x, cl.x), hmul2(hi.x, sl.x)); qh[0] = hadd2(hmul2(hi.x, ch.x), hmul2(lo.x, sh.x));
                    ql[2] = hsub2(hmul2(lo.y, cl.y), hmul2(hi.y, sl.y)); qh[2] = hadd2(hmul2(hi.y, ch.y), hmul2(lo.y, sh.y));
                    ql[4] = hsub2(hmul2(lo.z, cl.z), hmul2(hi.z, sl.z)); qh[4] = hadd2(hmul2(hi.z, ch.z), hmul2(lo.z, sh.z));
                    ql[6] = hsub2(hmul2(lo.w, cl.w), hmul2(hi.w, sl.w)); qh[6] = hadd2(hmul2(hi.w, ch.w), hmul2(lo.w, sh.w));
                }
            }
        }

        float s[64], o[kON];
        uint32_t pr[32];
        float ms0, ms1;
        const uint32_t sb4 = (sbase & 0x3FFFF) >> 4;
        const uint64_t dk0 = kDescK | sb4, dv0 = kDescV | (sb4 + (kSmemVOff >> 4));
        const uint32_t id_mine = __shfl_sync(0xffffffffu, 1 + wg, lane), id_other = __shfl_sync(0xffffffffu, 2 - wg, lane);

        {
            float s0[64];
            if (wg == 1) bar_sync(2, 256);
            mbar_wait(bar_full, 0);
            WG_FENCE();
            gemm_qk(s0, q, dk0);
            WG_COMMIT();
            {
                bar_sync(6 + wg, 128);
                const int t = threadIdx.x & 127;
                asm volatile("st.shared.v4.u32 [%0], {%1,%1,%1,%1};" ::"r"(sbase + kSmemVOff + wg * kVSlotBytes + 32768 + (t >> 3) * 1024 + (t & 7) * 144),
                             "r"(0x3F803F80u) : "memory");
                asm volatile("fence.proxy.async.shared::cta;" ::: "memory");
                __syncwarp();
                if (rel) mbar_arrive_cluster(rel_addr + 8 * (2 + wg));
            }
            wg_wait<0>();
            fence_regs(s0);
            bar_arrive(id_other, 256);
            if (rel) mbar_arrive_cluster(rel_addr);
            sched_boundary(p.zero[4]);
            row_max(s0, ms0, ms1);
            ms0 *= kScale; ms1 *= kScale;
            exp_tile<0, kExpSplit0>(s0, ms0, ms1);
            if (wg == 0) exp_tile<kExpSplit0, 16>(s0, ms0, ms1);
            mbar_wait(bar_full + 8, 0);
            bar_sync(id_mine, 256);
            WG_FENCE();
            gemm_qk(s, q, dk0 + (kTileBytes >> 4));
            WG_COMMIT();
            if (wg == 1) exp_tile<kExpSplit0, 16>(s0, ms0, ms1);
            pack_tile(pr, s0);
        }
#pragma unroll
        for (int i = 0; i < kON; i++) o[i] = 0.f;

        uint64_t dk = dk0, dv = dv0;
        auto finish = [&](int j, int ks, int vs, uint32_t vpar, uint32_t z) {
            mbar_wait(bar_full + 16 + 8 * vs, vpar);
            fence_regs(o); fence_regs(pr);
            WG_FENCE();
            gemm_pv(o, pr, dv + vs * (kVSlotBytes >> 4));
            WG_COMMIT();
            bar_arrive(id_other, 256);
            wg_wait<1>();
            fence_regs(s);
            if (rel) mbar_arrive_cluster(rel_addr + 8 * ks);
            exp_tile<0, kExpSplit>(s, ms0, ms1);
            sched_boundary(z);
            wg_wait<0>();
            fence_regs(o); fence_regs(s);
            if (rel) mbar_arrive_cluster(rel_addr + 16 + 8 * vs);
            exp_tile<kExpSplit, 16>(s, ms0, ms1);
            pack_tile(pr, s);
        };
        auto step = [&](int j, int ks, int vs, uint32_t kpar, uint32_t vpar, uint32_t z) {
            mbar_wait(bar_full + 8 * ks, kpar);
            bar_sync(id_mine, 256);
            fence_regs(s);
            WG_FENCE();
            gemm_qk(s, q, dk + ks * (kTileBytes >> 4));
            WG_COMMIT();
            finish(j, ks, vs, vpar, z);
        };
        finish(1, 1, 0, 0, p.zero[2]);
#pragma unroll 1
        for (int i = 1; i < 8; i++) {
            step(2 * i, 0, 1, i, i + 1, p.zero[0]);
            step(2 * i + 1, 1, 0, i, i, p.zero[1]);
            dk += p.zero[0]; dv += p.zero[0];
        }
        asm volatile("barrier.cluster.arrive.relaxed.aligned;" ::: "memory");

        __nv_bfloat16* op = p.out + (h * kS + qt * 128 + warp * 16 + g) * kD + 8 * c;
        bool ok;
        {
            float hi[36], lo[32];
            const float fz = __uint_as_float(p.zero[1]);
#pragma unroll
            for (int i = 0; i < 36; i++) hi[i] = o[32 + i] + fz;
#pragma unroll
            for (int i = 0; i < 32; i++) lo[i] = o[i] + fz;
            mbar_wait(bar_full + 24, 1);
            fence_regs(hi); fence_regs(lo); fence_regs(pr);
            WG_FENCE();
            const uint64_t d = dv0 + (kVSlotBytes >> 4);
#pragma unroll
            for (int kk = 0; kk < 8; kk++) wgmma_pv_hi(hi, pr[4 * kk], pr[4 * kk + 1], pr[4 * kk + 2], pr[4 * kk + 3], d + ((kk * 2048 + 16384) >> 4));
            WG_COMMIT();
#pragma unroll
            for (int kk = 0; kk < 8; kk++) wgmma_pv_lo(lo, pr[4 * kk], pr[4 * kk + 1], pr[4 * kk + 2], pr[4 * kk + 3], d + ((kk * 2048) >> 4));
            WG_COMMIT();
            wg_wait<1>();
            fence_regs(hi);
            const float i0 = rcp(hi[32]), i1 = rcp(hi[34]);
            uint4 u[4], v[4];
            store_half(op + 64, u, hi, 0, i0, i1);
            sched_boundary(p.zero[5]);
            wg_wait<0>();
            fence_regs(lo);
            store_half(op, v, lo, 0, i0, i1);
            sched_boundary(p.zero[6]);
            if (wg == 0) bar_sync(1, 256);
            ok = all_finite(u, v, __shfl_sync(0xffffffffu, 0u, lane)) && fminf(hi[32], hi[34]) >= 0.5f && hi[32] <= 1.2379400e27f &&
                 hi[34] <= 1.2379400e27f;
        }

        if (bar_red_or(3, 256, !ok)) {
            float m0 = -INFINITY, m1 = -INFINITY;
#pragma unroll
            for (int i = 0; i < kON; i++) o[i] = 0.f;
            const uint8_t* src = g_scratch + (size_t)h * kItems * kTileBytes;
#pragma unroll 1
            for (int j = 0; j < 16; j++) {
                if (threadIdx.x == 0) {
                    mbar_expect_tx(bar_fb, 2 * kTileBytes);
                    bulk_g2s(sbase, src + (size_t)(j == 0 ? 0 : 2 * j - 1) * kTileBytes, kTileBytes, bar_fb);
                    bulk_g2s(sbase + kSmemVOff, src + (size_t)(2 * j + 2) * kTileBytes, kTileBytes, bar_fb);
                }
                mbar_wait(bar_fb, j & 1);
                fence_regs(s);
                WG_FENCE();
                gemm_qk(s, q, dk0);
                WG_COMMIT();
                wg_wait<0>();
                fence_regs(s);
                float a0, a1;
                row_max(s, a0, a1);
                a0 = fmaxf(a0, m0); a1 = fmaxf(a1, m1);
                const float r0 = a0 == -INFINITY ? 0.f : a0, r1 = a1 == -INFINITY ? 0.f : a1;
                const float al0 = ex2((m0 - r0) * kScale), al1 = ex2((m1 - r1) * kScale);
                m0 = a0; m1 = a1;
#pragma unroll
                for (int i = 0; i < 64; i++) s[i] = ex2((s[i] - ((i & 2) ? r1 : r0)) * kScale);
                pack_tile(pr, s);
#pragma unroll
                for (int n = 0; n < kON / 4; n++) { o[4 * n] *= al0; o[4 * n + 1] *= al0; o[4 * n + 2] *= al1; o[4 * n + 3] *= al1; }
                fence_regs(o); fence_regs(pr);
                WG_FENCE();
                gemm_pv(o, pr, dv0);
                WG_COMMIT();
                wg_wait<0>();
                fence_regs(o);
                bar_sync(3, 256);
            }
            uint4 v[4];
            store_half(op, v, o, 0, 1.f / o[64], 1.f / o[66]);
            store_half(op + 64, v, o, 32, 1.f / o[64], 1.f / o[66]);
        }
        asm volatile("barrier.cluster.wait.aligned;" ::: "memory");
    }
}

}

extern "C" void kernel_launch(void* const* d_in, const int* in_sizes, int n_in, void* d_out, int out_size) {
    (void)in_sizes; (void)n_in; (void)out_size;
    Params p;
    p.q = (const __nv_bfloat16*)d_in[0];
    p.qk = (const int*)d_in[1];
    p.k_scales = (const __nv_bfloat16*)d_in[2];
    p.k_zeros = (const __nv_bfloat16*)d_in[3];
    p.qv = (const int*)d_in[4];
    p.v_scales = (const __nv_bfloat16*)d_in[5];
    p.v_zeros = (const __nv_bfloat16*)d_in[6];
    p.q_cos = (const __nv_bfloat16*)d_in[7];
    p.q_sin = (const __nv_bfloat16*)d_in[8];
    p.k_cos = (const __nv_bfloat16*)d_in[9];
    p.k_sin = (const __nv_bfloat16*)d_in[10];
    p.out = (__nv_bfloat16*)d_out;
    for (int i = 0; i < 8; i++) p.zero[i] = 0;
    p.t_v0 = 850; p.t_q = 440; p.dt_q = 640; p.t_next = 6050; p.dt_next = 430; p.t_k2 = 2300;
    p.t_poll = 2600; p.stagger = 43; p.lag_q = 140; p.catch_q = 23; p.t_tile1 = 5000; p.t_tile2 = 6000;
    static int co_resident = -1;
    if (co_resident < 0) {
        cudaFuncSetAttribute(attn_kernel, cudaFuncAttributeMaxDynamicSharedMemorySize, kSmemBytes);
        cudaLaunchConfig_t cfg = {};
        cfg.gridDim = dim3(kH * 16); cfg.blockDim = dim3(384); cfg.dynamicSmemBytes = kSmemBytes;
        cudaLaunchAttribute at;
        at.id = cudaLaunchAttributeClusterDimension;
        at.val.clusterDim.x = 2; at.val.clusterDim.y = 1; at.val.clusterDim.z = 1;
        cfg.attrs = &at; cfg.numAttrs = 1;
        int clusters = 0;
        co_resident = cudaOccupancyMaxActiveClusters(&clusters, attn_kernel, &cfg) == cudaSuccess && clusters >= kH * 8;
        (void)cudaGetLastError();
    }
    if (!co_resident) prefill_kernel<<<kItems * kH * 16, 128>>>(p);
    attn_kernel<<<kH * 16, 384, kSmemBytes>>>(p);
}
```
